```python
import torch

def _softmax(x, axis=-1):
    return torch.softmax(x, dim=axis)
def _gelu(x):
    return torch.nn.functional.gelu(x, approximate="tanh")
def _silu(x):
    return torch.nn.functional.silu(x)
def _sigmoid(x):
    return torch.sigmoid(x)
def _layernorm(x, axis=-1, eps=1e-5):
    m = x.mean(dim=axis, keepdim=True)
    v = x.var(dim=axis, keepdim=True, unbiased=False)
    return (x - m) / torch.sqrt(v + eps)
def _scatter_add(tgt, idx, src, axis=0):
    return tgt.clone().index_add_(axis, idx, src)
def _segment_sum(src, seg, n):
    out = torch.zeros((n,) + src.shape[1:], dtype=src.dtype)
    return out.index_add_(0, seg, src)
def _pad(x, pw):
    flat = tuple(v for pair in reversed(pw) for v in pair)
    return torch.nn.functional.pad(x, flat)

kernel_name = 'parallel_sum__ssm_conv_s4__glu_gated_bilinear__prompt'

def setup_inputs():

    _w = (lambda a: (lambda t: t.to(torch.bfloat16) if t.is_floating_point() else t)(torch.as_tensor(a)))
    def _A_setup():
        B, L, D, N = 1, 2048, 512, 128
        A_re = -(lambda _x: torch.exp(torch.as_tensor(_x)))((lambda *s: torch.randn(*s, dtype=torch.bfloat16) * 6.4)(D, N))
        A_im = torch.pi * (lambda *s: torch.randn(*s, dtype=torch.bfloat16) * 0.05)(D, N)
        B_re = (lambda *s: torch.randn(*s, dtype=torch.bfloat16) * 0.1)(D, N)
        B_im = (lambda *s: torch.randn(*s, dtype=torch.bfloat16) * 0.1)(D, N)
        C_re = (lambda *s: torch.randn(*s, dtype=torch.bfloat16) * 0.1)(D, N)
        C_im = (lambda *s: torch.randn(*s, dtype=torch.bfloat16) * 0.1)(D, N)
        log_dt = (lambda *s: torch.randn(*s, dtype=torch.bfloat16) * 0.05)(D) * 0.5 - 4.0
        Dskip = (lambda *s: torch.randn(*s, dtype=torch.bfloat16) * 0.05)(D)
        return {
            "u": _w((lambda *s: torch.randn(*s, dtype=torch.bfloat16) * 0.05)(B, L, D)),
            "A_re": _w(A_re),
            "A_im": _w(A_im),
            "B_re": _w(B_re),
            "B_im": _w(B_im),
            "C_re": _w(C_re),
            "C_im": _w(C_im),
            "log_dt": _w(log_dt),
            "Dskip": _w(Dskip),
        }
    _A_in = _A_setup()

    def _B_setup():
        B, S, D, F = 1, 2048, 512, 1376
        return {
            "x": _w((lambda *s: torch.randn(*s, dtype=torch.bfloat16) * 0.05)(B, S, D)),
            "w_gate": _w((lambda *s: torch.randn(*s, dtype=torch.bfloat16) * 0.4)(D, F) * (D ** -0.5)),
            "w_up": _w((lambda *s: torch.randn(*s, dtype=torch.bfloat16) * 0.4)(D, F) * (D ** -0.5)),
            "w_down": _w((lambda *s: torch.randn(*s, dtype=torch.bfloat16) * 0.4)(F, D) * (F ** -0.5)),
        }
    _B_in = _B_setup()

    return {
        "A_u": _A_in["u"],
        "A_A_re": _A_in["A_re"],
        "A_A_im": _A_in["A_im"],
        "A_B_re": _A_in["B_re"],
        "A_B_im": _A_in["B_im"],
        "A_C_re": _A_in["C_re"],
        "A_C_im": _A_in["C_im"],
        "A_log_dt": _A_in["log_dt"],
        "A_Dskip": _A_in["Dskip"],
        "B_x": _B_in["x"],
        "B_w_gate": _B_in["w_gate"],
        "B_w_up": _B_in["w_up"],
        "B_w_down": _B_in["w_down"],
    }

def reference(A_u, A_A_re, A_A_im, A_B_re, A_B_im, A_C_re, A_C_im, A_log_dt, A_Dskip, B_x, B_w_gate, B_w_up, B_w_down):
    def _A_ref(u, A_re, A_im, B_re, B_im, C_re, C_im, log_dt, Dskip):
        Bsz, L, D = u.shape
        dt = torch.exp(log_dt)[:, None]
        A = A_re + 1j * A_im
        Bc = B_re + 1j * B_im
        Cc = C_re + 1j * C_im
        logdA = dt * A
        dB = dt * Bc
        l = (lambda x, dt: x.to(dt))(torch.arange(L), A_re.dtype)
        P = torch.exp(logdA[:, :, None] * l[None, None, :])
        K = torch.einsum("dn,dnl,dn->dl", Cc, P, dB).real
        L2 = 2 * L
        Kp = _pad(K, ((0, 0), (0, L)))
        up = (lambda x, *d: x.permute(*d))(u, 0, 2, 1)
        up = _pad(up, ((0, 0), (0, 0), (0, L)))
        Kf = (lambda x, axes=(-2,-1): torch.fft.rfft2(x.float(), dim=axes))(Kp[:, None, :], axes=(-2, -1))
        Uf = (lambda x, axes=(-2,-1): torch.fft.rfft2(x.float(), dim=axes))(up[:, :, None, :], axes=(-2, -1))
        Yf = Uf * Kf[None, :, :, :]
        y = (lambda x, s, axes=(-2,-1): torch.fft.irfft2(x, s=s, dim=axes).to(torch.bfloat16))(Yf, (1, L2), axes=(-2, -1))[:, :, 0, :L]
        y = (lambda x, *d: x.permute(*d))(y, 0, 2, 1) + u * Dskip[None, None, :]
        return y

    def _B_ref(x, w_gate, w_up, w_down):
        g = torch.einsum("bsd,df->bsf", x, w_gate)
        u = torch.einsum("bsd,df->bsf", x, w_up)
        h = g * u
        return torch.einsum("bsf,fd->bsd", h, w_down)

    x = A_u
    xn = _layernorm(x, axis=-1)
    return x + _A_ref(xn, A_A_re, A_A_im, A_B_re, A_B_im, A_C_re, A_C_im, A_log_dt, A_Dskip) + _B_ref(xn, B_w_gate, B_w_up, B_w_down)
```

```cpp
#include <cuda_runtime.h>
#include <cuda_bf16.h>
#include <cuda.h>
#include <stdint.h>

namespace {

constexpr int SEQ = 2048, DM = 512, FF = 1376;
constexpr int NCTA = 132, NMAIN = 128;
constexpr int HT = 171;
constexpr int NFT = 22;

constexpr int G1_XB = 22528;
constexpr int G1_STAGE = 16384 + 2 * G1_XB;
constexpr int AUX = 3 * G1_STAGE;
constexpr int HRING = 0;
constexpr int SCR = 65536;
constexpr int WRING = 114688;
constexpr int UOFF = 163840;
constexpr int PSZ = 8256;
constexpr int TAB = AUX;
constexpr int KC = AUX + 4 * PSZ;
constexpr int MEANS = KC + 4 * 1408;
constexpr int R2S = MEANS + 1408;
constexpr int BARS = R2S + 512;
constexpr int B_F1 = 0, B_D1 = 8, B_F2 = 16, B_D2 = 38, B_STAT = 60, B_LND = 61, B_P = 62, B_U = 63, B_STG = 64,
              B_HST = 66, B_CVD = 67, B_X = 68, B_Y = 69, NBAR = 70;
constexpr int SMEM_BYTES = BARS + NBAR * 8;
static_assert(SMEM_BYTES <= 232448, "smem");

__device__ uint4 g_h[NFT * SEQ * 8];
__device__ uint4 g_u[NMAIN * 136 * 8];
__device__ uint2 g_y[16 * DM * 32];
__device__ float g_mean[SEQ], g_r2[SEQ];
__device__ unsigned g_cnt[16 * 32];
#define PROFT(i)

struct Params {
  const uint4* x;
  const uint32_t *are, *aim, *bre, *bim, *cre, *cim;
  const __nv_bfloat16 *logdt, *dskip;
  const uint8_t *wg, *wu, *wd;
};

template <int TA, int TB>
__device__ __forceinline__ void wgmma_ss_n176(float* d, uint64_t da, uint64_t db, int sc) {
  asm volatile("{\n.reg .pred p;\nsetp.ne.b32 p, %90, 0;\n"
      "wgmma.mma_async.sync.aligned.m64n176k16.f32.bf16.bf16 {"
      "%0, %1, %2, %3, %4, %5, %6, %7, %8, %9, %10, %11, %12, %13, %14, %15,"
      "%16, %17, %18, %19, %20, %21, %22, %23, %24, %25, %26, %27, %28, %29, %30, %31,"
      "%32, %33, %34, %35, %36, %37, %38, %39, %40, %41, %42, %43, %44, %45, %46, %47,"
      "%48, %49, %50, %51, %52, %53, %54, %55, %56, %57, %58, %59, %60, %61, %62, %63,"
      "%64, %65, %66, %67, %68, %69, %70, %71, %72, %73, %74, %75, %76, %77, %78, %79,"
      "%80, %81, %82, %83, %84, %85, %86, %87"
      "}, %88, %89, p, 1, 1, %91, %92;\n}\n"
    : "+f"(d[0]), "+f"(d[1]), "+f"(d[2]), "+f"(d[3]), "+f"(d[4]), "+f"(d[5]), "+f"(d[6]), "+f"(d[7]),
      "+f"(d[8]), "+f"(d[9]), "+f"(d[10]), "+f"(d[11]), "+f"(d[12]), "+f"(d[13]), "+f"(d[14]), "+f"(d[15]),
      "+f"(d[16]), "+f"(d[17]), "+f"(d[18]), "+f"(d[19]), "+f"(d[20]), "+f"(d[21]), "+f"(d[22]), "+f"(d[23]),
      "+f"(d[24]), "+f"(d[25]), "+f"(d[26]), "+f"(d[27]), "+f"(d[28]), "+f"(d[29]), "+f"(d[30]), "+f"(d[31]),
      "+f"(d[32]), "+f"(d[33]), "+f"(d[34]), "+f"(d[35]), "+f"(d[36]), "+f"(d[37]), "+f"(d[38]), "+f"(d[39]),
      "+f"(d[40]), "+f"(d[41]), "+f"(d[42]), "+f"(d[43]), "+f"(d[44]), "+f"(d[45]), "+f"(d[46]), "+f"(d[47]),
      "+f"(d[48]), "+f"(d[49]), "+f"(d[50]), "+f"(d[51]), "+f"(d[52]), "+f"(d[53]), "+f"(d[54]), "+f"(d[55]),
      "+f"(d[56]), "+f"(d[57]), "+f"(d[58]), "+f"(d[59]), "+f"(d[60]), "+f"(d[61]), "+f"(d[62]), "+f"(d[63]),
      "+f"(d[64]), "+f"(d[65]), "+f"(d[66]), "+f"(d[67]), "+f"(d[68]), "+f"(d[69]), "+f"(d[70]), "+f"(d[71]),
      "+f"(d[72]), "+f"(d[73]), "+f"(d[74]), "+f"(d[75]), "+f"(d[76]), "+f"(d[77]), "+f"(d[78]), "+f"(d[79]),
      "+f"(d[80]), "+f"(d[81]), "+f"(d[82]), "+f"(d[83]), "+f"(d[84]), "+f"(d[85]), "+f"(d[86]), "+f"(d[87])
    : "l"(da), "l"(db), "r"(sc), "n"(TA), "n"(TB));
}
template <int TA, int TB>
__device__ __forceinline__ void wgmma_ss_n64(float* d, uint64_t da, uint64_t db, int sc) {
  asm volatile("{\n.reg .pred p;\nsetp.ne.b32 p, %34, 0;\n"
      "wgmma.mma_async.sync.aligned.m64n64k16.f32.bf16.bf16 {"
      "%0, %1, %2, %3, %4, %5, %6, %7, %8, %9, %10, %11, %12, %13, %14, %15,"
      "%16, %17, %18, %19, %20, %21, %22, %23, %24, %25, %26, %27, %28, %29, %30, %31"
      "}, %32, %33, p, 1, 1, %35, %36;\n}\n"
    : "+f"(d[0]), "+f"(d[1]), "+f"(d[2]), "+f"(d[3]), "+f"(d[4]), "+f"(d[5]), "+f"(d[6]), "+f"(d[7]),
      "+f"(d[8]), "+f"(d[9]), "+f"(d[10]), "+f"(d[11]), "+f"(d[12]), "+f"(d[13]), "+f"(d[14]), "+f"(d[15]),
      "+f"(d[16]), "+f"(d[17]), "+f"(d[18]), "+f"(d[19]), "+f"(d[20]), "+f"(d[21]), "+f"(d[22]), "+f"(d[23]),
      "+f"(d[24]), "+f"(d[25]), "+f"(d[26]), "+f"(d[27]), "+f"(d[28]), "+f"(d[29]), "+f"(d[30]), "+f"(d[31])
    : "l"(da), "l"(db), "r"(sc), "n"(TA), "n"(TB));
}
template <int TA, int TB>
__device__ __forceinline__ void wgmma_ss_n48(float* d, uint64_t da, uint64_t db, int sc) {
  asm volatile("{\n.reg .pred p;\nsetp.ne.b32 p, %26, 0;\n"
      "wgmma.mma_async.sync.aligned.m64n48k16.f32.bf16.bf16 {"
      "%0, %1, %2, %3, %4, %5, %6, %7, %8, %9, %10, %11, %12, %13, %14, %15,"
      "%16, %17, %18, %19, %20, %21, %22, %23"
      "}, %24, %25, p, 1, 1, %27, %28;\n}\n"
    : "+f"(d[0]), "+f"(d[1]), "+f"(d[2]), "+f"(d[3]), "+f"(d[4]), "+f"(d[5]), "+f"(d[6]), "+f"(d[7]),
      "+f"(d[8]), "+f"(d[9]), "+f"(d[10]), "+f"(d[11]), "+f"(d[12]), "+f"(d[13]), "+f"(d[14]), "+f"(d[15]),
      "+f"(d[16]), "+f"(d[17]), "+f"(d[18]), "+f"(d[19]), "+f"(d[20]), "+f"(d[21]), "+f"(d[22]), "+f"(d[23])
    : "l"(da), "l"(db), "r"(sc), "n"(TA), "n"(TB));
}
template <int TB>
__device__ __forceinline__ void wgmma_rs_n32(float* d, uint32_t a0, uint32_t a1, uint32_t a2, uint32_t a3, uint64_t db, int sc) {
  asm volatile("{\n.reg .pred p;\nsetp.ne.b32 p, %21, 0;\n"
      "wgmma.mma_async.sync.aligned.m64n32k16.f32.bf16.bf16 {"
      "%0, %1, %2, %3, %4, %5, %6, %7, %8, %9, %10, %11, %12, %13, %14, %15"
      "}, {%16,%17,%18,%19}, %20, p, 1, 1, %22;\n}\n"
    : "+f"(d[0]), "+f"(d[1]), "+f"(d[2]), "+f"(d[3]), "+f"(d[4]), "+f"(d[5]), "+f"(d[6]), "+f"(d[7]),
      "+f"(d[8]), "+f"(d[9]), "+f"(d[10]), "+f"(d[11]), "+f"(d[12]), "+f"(d[13]), "+f"(d[14]), "+f"(d[15])
    : "r"(a0), "r"(a1), "r"(a2), "r"(a3), "l"(db), "r"(sc), "n"(TB));
}
#define WG_FENCE() asm volatile("wgmma.fence.sync.aligned;" ::: "memory")
#define WG_COMMIT() asm volatile("wgmma.commit_group.sync.aligned;" ::: "memory")
template <int N> __device__ __forceinline__ void wg_wait() { asm volatile("wgmma.wait_group.sync.aligned %0;" ::"n"(N) : "memory"); }
template <int N> __device__ __forceinline__ void pin(float* a) {
#pragma unroll
  for (int i = 0; i < N; i++) asm volatile("" : "+f"(a[i])::"memory");
}
__device__ __forceinline__ uint64_t desc128(uint32_t addr) {
  return (uint64_t)((addr & 0x3FFFF) >> 4) | ((uint64_t)1 << 16) | ((uint64_t)64 << 32) | ((uint64_t)1 << 62);
}
__device__ __forceinline__ void mbar_init(uint32_t bar, uint32_t cnt) { asm volatile("mbarrier.init.shared::cta.b64 [%0], %1;" ::"r"(bar), "r"(cnt) : "memory"); }
__device__ __forceinline__ void mbar_arrive(uint32_t bar) { asm volatile("mbarrier.arrive.shared::cta.b64 _, [%0];" ::"r"(bar) : "memory"); }
__device__ __forceinline__ void mbar_expect(uint32_t bar, uint32_t bytes) { asm volatile("mbarrier.arrive.expect_tx.shared::cta.b64 _, [%0], %1;" ::"r"(bar), "r"(bytes) : "memory"); }
__device__ __forceinline__ void mbar_wait(uint32_t bar) {
  asm volatile(
      "{\n.reg .pred p;\n.reg .u32 c;\nmov.u32 c, 0;\n"
      "W_%=:\nmbarrier.try_wait.parity.shared::cta.b64 p, [%0], 0;\n@p bra D_%=;\n"
      "add.u32 c, c, 1;\nsetp.lt.u32 p, c, 0x40000;\n@p bra W_%=;\ntrap;\nD_%=:\n}\n" ::"r"(bar) : "memory");
}
__device__ __forceinline__ void flag_wait(const unsigned* p, unsigned target) {
  asm volatile(
      "{\n.reg .pred p;\n.reg .u32 c, v;\nmov.u32 c, 0;\n"
      "W_%=:\nld.acquire.gpu.global.u32 v, [%0];\nsetp.ge.u32 p, v, %1;\n@p bra D_%=;\n"
      "add.u32 c, c, 1;\nsetp.lt.u32 p, c, 0x100000;\n@p bra W_%=;\ntrap;\nD_%=:\n}\n" ::"l"(p), "r"(target) : "memory");
}
__device__ __forceinline__ void flag_arrive(unsigned* p) { asm volatile("red.release.gpu.global.add.u32 [%0], 1;" ::"l"(p) : "memory"); }
__device__ __forceinline__ void fence_async_smem() { asm volatile("fence.proxy.async.shared::cta;" ::: "memory"); }
__device__ __forceinline__ void fence_async_all() { asm volatile("fence.proxy.async;" ::: "memory"); }
__device__ __forceinline__ void bar_sync(int id) { asm volatile("bar.sync %0, 128;" ::"r"(id) : "memory"); }
__device__ __forceinline__ bool elect() {
  uint32_t e;
  asm volatile("{\n.reg .pred p;\nelect.sync _|p, 0xffffffff;\nselp.u32 %0, 1, 0, p;\n}\n" : "=r"(e));
  return e;
}
__device__ __forceinline__ void tma2d(uint32_t dst, const CUtensorMap* tm, int c0, int c1, uint32_t bar) {
  asm volatile("cp.async.bulk.tensor.2d.shared::cluster.global.mbarrier::complete_tx::bytes [%0], [%1, {%3, %4}], [%2];"
               ::"r"(dst), "l"(tm), "r"(bar), "r"(c0), "r"(c1) : "memory");
}
__device__ __forceinline__ void bulk_ld(uint32_t dst, const void* src, uint32_t bytes, uint32_t bar) {
  asm volatile("cp.async.bulk.shared::cluster.global.mbarrier::complete_tx::bytes [%0], [%1], %2, [%3];"
               ::"r"(dst), "l"(src), "r"(bytes), "r"(bar) : "memory");
}
__device__ __forceinline__ uint32_t lds32(uint32_t a) { uint32_t v; asm volatile("ld.shared.u32 %0, [%1];" : "=r"(v) : "r"(a)); return v; }
__device__ __forceinline__ uint32_t lds16(uint32_t a) { uint16_t v; asm volatile("ld.shared.u16 %0, [%1];" : "=h"(v) : "r"(a)); return v; }
__device__ __forceinline__ void sts32(uint32_t a, uint32_t v) { asm volatile("st.shared.u32 [%0], %1;" ::"r"(a), "r"(v) : "memory"); }
__device__ __forceinline__ void sts16(uint32_t a, uint32_t v) { asm volatile("st.shared.u16 [%0], %1;" ::"r"(a), "h"((uint16_t)v) : "memory"); }
__device__ __forceinline__ void sts128(uint32_t a, uint32_t x, uint32_t y, uint32_t z, uint32_t w) {
  asm volatile("st.shared.v4.u32 [%0], {%1,%2,%3,%4};" ::"r"(a), "r"(x), "r"(y), "r"(z), "r"(w) : "memory");
}
__device__ __forceinline__ uint32_t pack(float lo, float hi) { uint32_t r; asm("cvt.rn.bf16x2.f32 %0, %1, %2;" : "=r"(r) : "f"(hi), "f"(lo)); return r; }
__device__ __forceinline__ float blo(uint32_t v) { return __uint_as_float(v << 16); }
__device__ __forceinline__ float bhi(uint32_t v) { return __uint_as_float(v & 0xffff0000u); }
__device__ __forceinline__ float rbf(float v) { return __bfloat162float(__float2bfloat16_rn(v)); }

struct cplx { float x, y; };
__device__ __forceinline__ cplx cmul(cplx a, cplx b) { return {fmaf(a.x, b.x, -a.y * b.y), fmaf(a.x, b.y, a.y * b.x)}; }
__device__ __forceinline__ cplx csq(cplx a) { return {fmaf(a.x, a.x, -a.y * a.y), (a.x + a.x) * a.y}; }
__device__ __forceinline__ cplx cpow(float al, float th, float E) {
  float m, p = th * E;
  asm("ex2.approx.ftz.f32 %0, %1;" : "=f"(m) : "f"(al * E));
  p = (p - rintf(p)) * 6.283185307179586f;
  return {m * __cosf(p), m * __sinf(p)};
}

template <int Q> __device__ __forceinline__ void conv_loadA(uint32_t* R, uint32_t pa, uint32_t zero) {
  R[2] = lds32(pa + (512 * Q) * 4);
#pragma unroll
  for (int s = 0; s < 8; s++) {
    R[4 * s] = lds32(pa + (512 * Q + 16 * s + 8) * 4);
    R[4 * s + 1] = lds32(pa + (512 * Q + 16 * s + 16) * 4);
  }
#pragma unroll
  for (int s = 0; s < 8; s++) {
    asm volatile("or.b32 %0, %1, %2;" : "=r"(R[4 * s + 3]) : "r"(R[4 * s]), "r"(zero));
    if (s < 7) asm volatile("or.b32 %0, %1, %2;" : "=r"(R[4 * s + 6]) : "r"(R[4 * s + 1]), "r"(zero));
  }
}
template <int Q, int S0, int S1> __device__ __forceinline__ void conv_mma(float (*acc)[16], const uint32_t* R, uint64_t db) {
#pragma unroll
  for (int s = S0; s < S1; s++) {
#pragma unroll
    for (int B = Q; B < 4; B++)
      wgmma_rs_n32<0>(acc[B], R[4 * s], R[4 * s + 1], R[4 * s + 2], R[4 * s + 3], db + (8 + 32 * (B - Q) - s) * 8, (Q == 0 && s == 0) ? 0 : 1);
  }
}
template <int B> __device__ __forceinline__ void conv_send(float* a, uint32_t sb, int w) {
  pin<16>(a);
#pragma unroll
  for (int r = 1; r < 4; r++)
    if (B < 3 || r + w < 4)
      asm volatile("st.shared.v4.f32 [%0], {%1,%2,%3,%4};" ::"r"(sb + ((4 * B + r) * 3 + (r - 1)) * 512), "f"(a[4 * r]), "f"(a[4 * r + 1]), "f"(a[4 * r + 2]), "f"(a[4 * r + 3]) : "memory");
}

__global__ void __launch_bounds__(512, 1)
fused_kernel(const __grid_constant__ CUtensorMap tm_x, const __grid_constant__ CUtensorMap tm_wg, const __grid_constant__ CUtensorMap tm_wu,
             const __grid_constant__ CUtensorMap tm_wd, const __grid_constant__ CUtensorMap tm_x2, const __grid_constant__ CUtensorMap tm_out,
             const Params p) {
  extern __shared__ __align__(1024) uint8_t smem_raw[];
  uint32_t sm = (uint32_t)__cvta_generic_to_shared(smem_raw);
  const uint32_t bars = sm + BARS;
  const int warp = __shfl_sync(0xffffffffu, threadIdx.x >> 5, 0);
  const int lane = threadIdx.x & 31;

  int lt2;
  {
    uint32_t smid, nsm;
    asm volatile("mov.u32 %0, %%smid;" : "=r"(smid));
    asm volatile("mov.u32 %0, %%nsmid;" : "=r"(nsm));
    const int id = (nsm == NCTA) ? (int)smid : (int)blockIdx.x;
    const int tpc = id >> 1;
    int lt;
    if (tpc < 32) lt = (tpc & 7) ? ((tpc & 7) - 1) * 8 + (tpc >> 3) : 56 + (tpc >> 3);
    else if (tpc < 60) lt = ((tpc - 32) % 7) * 8 + 4 + (tpc - 32) / 7;
    else lt = tpc < 62 ? tpc + 4 : tpc - 2;
    lt2 = lt * 2 + (id & 1);
  }
  const int ft = (lt2 >> 1) % NFT;
  const int tc = ((lt2 >> 1) / NFT) * 2 + (lt2 & 1);
  const bool mainc = lt2 < NMAIN;
  const int mt = (lt2 >> 4) * 2 + (lt2 & 1), dt = (lt2 >> 1) & 7;

  if (warp == 12) {
    if (elect()) {
#pragma unroll
      for (int s = 0; s < 3; s++) mbar_init(bars + (B_F1 + s) * 8, 1);
      fence_async_smem();
#pragma unroll
      for (int s = 0; s < 3; s++) {
        const uint32_t st = sm + s * G1_STAGE, b = bars + (B_F1 + s) * 8;
        mbar_expect(b, 16384 + 2 * HT * 128);
        tma2d(st, &tm_wg, ft * 64, s * 64, b);
        tma2d(st + 16384, &tm_x, s * 64, tc * 2 * HT, b);
        tma2d(st + 8192, &tm_wu, ft * 64, s * 64, b);
        tma2d(st + 16384 + G1_XB, &tm_x, s * 64, tc * 2 * HT + HT, b);
      }
    }
  } else if (warp < 3) {
    const int i = threadIdx.x;
    if (i >= 3 && i < NBAR) {
      uint32_t c = 1;
      if ((i >= B_D1 && i < B_F2) || (i >= B_D2 && i < B_STAT) || i == B_CVD) c = 8;
      else if (i >= B_F2 && i < B_D2) c = 2;
      else if (i == B_LND || i == B_P || i == B_STG || i == B_STG + 1) c = 4;
      mbar_init(bars + i * 8, c);
    }
    fence_async_smem();
  } else if (warp < 5) {
    const int i = threadIdx.x - 96;
    if (i < 48) {
      const int r = i >> 3;
      sts128(sm + (r >> 1) * G1_STAGE + 16384 + (r & 1) * G1_XB + 175 * 128 + (i & 7) * 16, 0x3F803F80u, 0x3F803F80u, 0x3F803F80u, 0x3F803F80u);
    }
    fence_async_smem();
  }
  __syncthreads();

  if (warp < 8) {
    asm volatile("setmaxnreg.inc.sync.aligned.u32 208;");
    const int wg = warp >> 2, w = warp & 3, g = lane >> 2, tq = lane & 3;
    {
      float ag[88], au[88];
      uint32_t st = sm;
#pragma unroll 1
      for (int kb = 0; kb < 8; kb++) {
        const uint64_t da = desc128(st), db = desc128(st + 16384 + wg * G1_XB);
        mbar_wait(bars + (B_F1 + kb) * 8);
        if (kb == 0) PROFT(wg * 16 + 0);
        WG_FENCE();
        wgmma_ss_n176<1, 0>(ag, da, db, kb);
        wgmma_ss_n176<1, 0>(au, da + 512, db, kb);
        WG_COMMIT();
        wg_wait<1>();
        if (kb > 0 && lane == 0) mbar_arrive(bars + (B_D1 + kb - 1) * 8);
#pragma unroll
        for (int ks = 1; ks < 4; ks++) {
          wgmma_ss_n176<1, 0>(ag, da + ks * 128, db + ks * 2, 1);
          wgmma_ss_n176<1, 0>(au, da + 512 + ks * 128, db + ks * 2, 1);
        }
        WG_COMMIT();
        st += G1_STAGE;
        if (st == sm + AUX) st = sm;
      }
      wg_wait<0>();
      pin<88>(ag);
      pin<88>(au);
      if (lane == 0) mbar_arrive(bars + (B_D1 + 7) * 8);
      PROFT(wg * 16 + 1);
      mbar_wait(bars + B_STAT * 8);
      mbar_wait(bars + (B_D1 + 6) * 8);
      PROFT(wg * 16 + 2);
      const float cg0 = __shfl_sync(0xffffffffu, ag[85], lane | 3), cg1 = __shfl_sync(0xffffffffu, ag[87], lane | 3);
      const float cu0 = __shfl_sync(0xffffffffu, au[85], lane | 3), cu1 = __shfl_sync(0xffffffffu, au[87], lane | 3);
      const int tok0 = (tc * 2 + wg) * HT;
      const uint32_t sa = sm + HRING + wg * G1_XB + ((lane & 7) + (lane >> 4) * 8) * 128 + (((2 * w + ((lane >> 3) & 1)) ^ ((tok0 + lane) & 7)) << 4);
      const uint32_t ma = sm + MEANS + wg * 704 + tq * 8;
#pragma unroll
      for (int jp = 0; jp < 11; jp++) {
        uint32_t r[4];
#pragma unroll
        for (int e = 0; e < 2; e++) {
          const int j = 2 * jp + e;
          float m0, m1;
          asm volatile("ld.shared.v2.f32 {%0,%1}, [%2];" : "=f"(m0), "=f"(m1) : "r"(ma + j * 32));
          r[2 * e] = pack(fmaf(m0, cg0, ag[4 * j]) * fmaf(m0, cu0, au[4 * j]), fmaf(m1, cg0, ag[4 * j + 1]) * fmaf(m1, cu0, au[4 * j + 1]));
          r[2 * e + 1] = pack(fmaf(m0, cg1, ag[4 * j + 2]) * fmaf(m0, cu1, au[4 * j + 2]), fmaf(m1, cg1, ag[4 * j + 3]) * fmaf(m1, cu1, au[4 * j + 3]));
        }
        asm volatile("stmatrix.sync.aligned.m8n8.x4.trans.shared.b16 [%0], {%1,%2,%3,%4};" ::"r"(sa + jp * 2048), "r"(r[0]), "r"(r[1]), "r"(r[2]), "r"(r[3]) : "memory");
      }
      fence_async_smem();
      __syncwarp();
      if (lane == 0) mbar_arrive(bars + (B_STG + wg) * 8);
      PROFT(wg * 16 + 3);
    }
    if (mainc) {
      mbar_wait(bars + B_P * 8);
      mbar_wait(bars + B_U * 8);
      mbar_wait(bars + (B_D1 + 7) * 8);
      PROFT(wg * 16 + 4);
      {
        const uint32_t sb = sm + SCR + wg * 24576 + w * 1536 + lane * 16;
        const uint32_t zero = lds32(sm + UOFF);
        uint32_t pa = sm + TAB + wg * 2 * PSZ + (8 + 128 * w + g - 2 * tq) * 4;
        uint2* yo = g_y + (w * DM + lt2 * 4 + wg * 2) * 32 + (lane ^ ((2 * lt2 + wg) & 3));
#pragma unroll 1
        for (int cc = 0; cc < 2; cc++) {
          const uint64_t db = desc128(sm + UOFF + (wg * 2 + cc) * 32);
          float acc[4][16];
          uint32_t R0[32], R1[32];
          conv_loadA<0>(R0, pa, zero);
          WG_FENCE(); conv_mma<0, 0, 2>(acc, R0, db);
          conv_loadA<1>(R1, pa, zero);
          conv_mma<0, 2, 8>(acc, R0, db); WG_COMMIT();
          WG_FENCE(); conv_mma<1, 0, 1>(acc, R1, db); WG_COMMIT();
          wg_wait<1>();
          if (cc) bar_sync(1 + wg);
          conv_loadA<2>(R0, pa, zero);
          conv_mma<1, 1, 4>(acc, R1, db);
          conv_send<0>(acc[0], sb, w);
          conv_mma<1, 4, 8>(acc, R1, db); WG_COMMIT();
          WG_FENCE(); conv_mma<2, 0, 1>(acc, R0, db); WG_COMMIT();
          wg_wait<1>();
          conv_loadA<3>(R1, pa, zero);
          conv_mma<2, 1, 4>(acc, R0, db);
          conv_send<1>(acc[1], sb, w);
          conv_mma<2, 4, 8>(acc, R0, db); WG_COMMIT();
          WG_FENCE(); conv_mma<3, 0, 2>(acc, R1, db); WG_COMMIT();
          wg_wait<1>();
          conv_send<2>(acc[2], sb, w);
          conv_mma<3, 2, 8>(acc, R1, db); WG_COMMIT();
          wg_wait<0>();
          conv_send<3>(acc[3], sb, w);
          bar_sync(1 + wg);
#pragma unroll
          for (int k = 0; k < 4; k++) {
#pragma unroll
            for (int r = 1; r < 4; r++) {
              if (k > 0 || r <= w) {
                float a, b, c, d;
                asm volatile("ld.shared.v4.f32 {%0,%1,%2,%3}, [%4];" : "=f"(a), "=f"(b), "=f"(c), "=f"(d) : "r"(sb + (12 * k + r - 1) * 512) : "memory");
                acc[k][0] += a; acc[k][1] += b; acc[k][2] += c; acc[k][3] += d;
              }
            }
            const uint32_t p0 = pack(acc[k][0], acc[k][2]), p1 = pack(acc[k][1], acc[k][3]);
            yo[k * 4 * DM * 32] = lane < 16 ? make_uint2(p0, p1) : make_uint2(p1, p0);
          }
          pa += PSZ;
          yo += 32;
          PROFT(wg * 16 + 5 + cc);
        }
        fence_async_smem();
        __syncwarp();
        if (lane == 0) mbar_arrive(bars + B_CVD * 8);
      }
      float acc[32];
      {
        uint32_t hs = sm + HRING + wg * 8192, ws = sm + WRING + 8192;
#pragma unroll 1
        for (int kb = 0; kb < NFT; kb++) {
          const uint64_t da = desc128(hs), db = desc128(ws);
          mbar_wait(bars + (B_F2 + kb) * 8);
          if (kb == 0) PROFT(wg * 16 + 7);
          WG_FENCE();
          wgmma_ss_n64<0, 1>(acc, da, db, kb);
          wgmma_ss_n64<0, 1>(acc, da + 2, db + 128, 1);
          if (kb < NFT - 1) {
            wgmma_ss_n64<0, 1>(acc, da + 4, db + 256, 1);
            wgmma_ss_n64<0, 1>(acc, da + 6, db + 384, 1);
          }
          WG_COMMIT();
          wg_wait<1>();
          if (kb > 0 && lane == 0) mbar_arrive(bars + (B_D2 + kb - 1) * 8);
          hs += 16384;
          if (hs >= sm + WRING) hs -= WRING;
          ws += 8192;
          if (ws == sm + UOFF) ws = sm + WRING;
        }
      }
      mbar_wait(bars + B_X * 8);
      mbar_wait(bars + B_Y * 8);
      wg_wait<0>();
      pin<32>(acc);
      PROFT(wg * 16 + 8);
      {
        const int row = wg * 64 + w * 16;
        const float r0 = __uint_as_float(lds32(sm + R2S + (row + g) * 4)), r1 = __uint_as_float(lds32(sm + R2S + (row + g + 8) * 4));
        const uint32_t xa = sm + TAB + (row + (lane & 15)) * 128;
        const uint32_t ya = sm + TAB + 16384 + tq * 512 + (8 * g + 2 * ((warp >> 1) ^ tq) + ((warp & 1) ^ (g >> 2))) * 4;
#pragma unroll
        for (int jp = 0; jp < 4; jp++) {
          uint32_t xr[4];
          const uint32_t a = xa + (((2 * jp + (lane >> 4)) ^ (lane & 7)) << 4);
          asm volatile("ldmatrix.sync.aligned.m8n8.x4.shared.b16 {%0,%1,%2,%3}, [%4];" : "=r"(xr[0]), "=r"(xr[1]), "=r"(xr[2]), "=r"(xr[3]) : "r"(a) : "memory");
#pragma unroll
          for (int e = 0; e < 2; e++) {
            const int j = 2 * jp + e;
            const uint32_t y0 = lds32(ya + j * 2048), y1 = lds32(ya + j * 2048 + 256);
            xr[2 * e] = pack(fmaf(r0, acc[4 * j], blo(xr[2 * e]) + blo(y0)), fmaf(r0, acc[4 * j + 1], bhi(xr[2 * e]) + blo(y1)));
            xr[2 * e + 1] = pack(fmaf(r1, acc[4 * j + 2], blo(xr[2 * e + 1]) + bhi(y0)), fmaf(r1, acc[4 * j + 3], bhi(xr[2 * e + 1]) + bhi(y1)));
          }
          asm volatile("stmatrix.sync.aligned.m8n8.x4.shared.b16 [%0], {%1,%2,%3,%4};" ::"r"(a), "r"(xr[0]), "r"(xr[1]), "r"(xr[2]), "r"(xr[3]) : "memory");
        }
        fence_async_smem();
        __syncwarp();
        if (elect()) {
          asm volatile("cp.async.bulk.tensor.2d.global.shared::cta.bulk_group [%0, {%2, %3}], [%1];"
                       ::"l"(&tm_out), "r"(sm + TAB + row * 128), "r"(dt * 64), "r"(mt * 128 + row) : "memory");
          asm volatile("cp.async.bulk.commit_group;" ::: "memory");
          asm volatile("cp.async.bulk.wait_group.read 0;" ::: "memory");
        }
        PROFT(wg * 16 + 9);
      }
    }
  } else if (warp < 12) {
    asm volatile("setmaxnreg.dec.sync.aligned.u32 72;");
    if (mainc) {
      const int w = warp & 3, tid = threadIdx.x & 127;
      uint32_t prm[2][6];
      float ldt[2], dsk[2];
      {
        uint4 v[4][2];
#pragma unroll
        for (int r = 0; r < 4; r++) {
          const uint4* src = p.x + (lt2 * 16 + w * 4 + r) * 64 + lane;
          v[r][0] = __ldg(src);
          v[r][1] = __ldg(src + 32);
        }
#pragma unroll
        for (int q = 0; q < 2; q++) {
          const int d = lt2 * 4 + q * 2 + (w >> 1), o = d * 64 + (tid & 63);
          prm[q][0] = __ldg(p.are + o); prm[q][1] = __ldg(p.aim + o); prm[q][2] = __ldg(p.bre + o);
          prm[q][3] = __ldg(p.bim + o); prm[q][4] = __ldg(p.cre + o); prm[q][5] = __ldg(p.cim + o);
          ldt[q] = __bfloat162float(p.logdt[d]);
          dsk[q] = __bfloat162float(p.dskip[d]);
        }
#pragma unroll
        for (int r = 0; r < 4; r++) {
          uint32_t u[8] = {v[r][0].x, v[r][0].y, v[r][0].z, v[r][0].w, v[r][1].x, v[r][1].y, v[r][1].z, v[r][1].w};
          float s = 0.f;
#pragma unroll
          for (int i = 0; i < 8; i++) s += blo(u[i]) + bhi(u[i]);
#pragma unroll
          for (int o = 16; o; o >>= 1) s += __shfl_xor_sync(0xffffffffu, s, o);
          const float mean = s * (1.f / DM);
          float q = 0.f;
#pragma unroll
          for (int i = 0; i < 8; i++) { const float a = blo(u[i]) - mean, b = bhi(u[i]) - mean; q = fmaf(a, a, fmaf(b, b, q)); }
#pragma unroll
          for (int o = 16; o; o >>= 1) q += __shfl_xor_sync(0xffffffffu, q, o);
          const float mb = rbf(mean);
          const float inv = 1.f / rbf(sqrtf(rbf(rbf(q * (1.f / DM)) + 1e-5f)));
#pragma unroll
          for (int i = 0; i < 8; i++) { const uint32_t c = pack(blo(u[i]) - mb, bhi(u[i]) - mb); u[i] = pack(blo(c) * inv, bhi(c) * inv); }
          const uint32_t a = sm + TAB + (w * 4 + r) * 1024 + lane * 16;
          sts128(a, u[0], u[1], u[2], u[3]);
          sts128(a + 512, u[4], u[5], u[6], u[7]);
          if (lane == 0) { g_mean[lt2 * 16 + w * 4 + r] = -mb; g_r2[lt2 * 16 + w * 4 + r] = inv * inv; }
        }
        bar_sync(3);
        uint4* dst = g_u + (tid * 136 + 8 + lt2) * 8;
#pragma unroll
        for (int hb = 0; hb < 2; hb++) {
          uint32_t a[8], b[8];
#pragma unroll
          for (int r = 0; r < 8; r++)
            asm volatile("ld.shared.v2.u32 {%0,%1}, [%2];" : "=r"(a[r]), "=r"(b[r]) : "r"(sm + TAB + (hb * 8 + r) * 1024 + tid * 8) : "memory");
          const int sw = lt2 & 7;
          dst[(0 + hb) ^ sw] = make_uint4(__byte_perm(a[0], a[1], 0x5410), __byte_perm(a[2], a[3], 0x5410), __byte_perm(a[4], a[5], 0x5410), __byte_perm(a[6], a[7], 0x5410));
          dst[(2 + hb) ^ sw] = make_uint4(__byte_perm(a[0], a[1], 0x7632), __byte_perm(a[2], a[3], 0x7632), __byte_perm(a[4], a[5], 0x7632), __byte_perm(a[6], a[7], 0x7632));
          dst[(4 + hb) ^ sw] = make_uint4(__byte_perm(b[0], b[1], 0x5410), __byte_perm(b[2], b[3], 0x5410), __byte_perm(b[4], b[5], 0x5410), __byte_perm(b[6], b[7], 0x5410));
          dst[(6 + hb) ^ sw] = make_uint4(__byte_perm(b[0], b[1], 0x7632), __byte_perm(b[2], b[3], 0x7632), __byte_perm(b[4], b[5], 0x7632), __byte_perm(b[6], b[7], 0x7632));
        }
        __syncwarp();
        if (lane == 0) mbar_arrive(bars + B_LND * 8);
        PROFT(32);
      }
      const uint32_t ta = sm + TAB + (w & 1) * 8192 + (w >> 1) * 4096, tb = sm + TAB + 16384 + (w & 1) * 6144 + (w >> 1) * 3072;
      const uint32_t l4 = lane * 4;
      float acc[24];
#pragma unroll 1
      for (int r = 0; r < 4; r++) {
        if (r == 2) {
#pragma unroll
          for (int i = 0; i < 6; i++) prm[0][i] = prm[1][i];
          ldt[0] = ldt[1]; dsk[0] = dsk[1];
        }
        const int sh = (r & 1) ? 0 : 16;
        const float dtv = rbf(expf(ldt[0]));
        const float al = dtv * bhi(prm[0][0] << sh) * 1.4426950408889634f, th = dtv * bhi(prm[0][1] << sh) * 0.15915494309189535f;
        const cplx c = cmul({bhi(prm[0][4] << sh), bhi(prm[0][5] << sh)}, {dtv * bhi(prm[0][2] << sh), dtv * bhi(prm[0][3] << sh)});
        const cplx z1 = cpow(al, th, 1.f), z8 = cpow(al, th, 8.f), z64 = cpow(al, th, 64.f), w1 = cpow(al, th, 256.f);
        bar_sync(3);
#define STB(row, v) sts32(tb + (row) * 128 + (l4 ^ (((row) & 7) << 4)), pack((v).x, (v).y))
        {
          const cplx z2 = csq(z1), z3 = cmul(z2, z1), z4 = csq(z2), z6 = csq(z3);
          sts32(tb + l4, 0x00003F80u);
          STB(1, z1); STB(2, z2); STB(3, z3); STB(4, z4); STB(5, cmul(z4, z1)); STB(6, z6); STB(7, cmul(z4, z3));
          const cplx w2 = csq(w1), w3 = cmul(w2, w1), w4 = csq(w2);
          STB(8, w1); STB(9, cmul(w1, z2)); STB(10, cmul(w1, z4)); STB(11, cmul(w1, z6));
          STB(12, w2); STB(13, cmul(w2, z4)); STB(14, w3); STB(15, cmul(w3, z4));
          STB(16, w4); STB(17, cmul(w4, w1)); STB(18, csq(w3)); STB(19, cmul(w4, w3)); STB(20, csq(w4));
        }
#undef STB
        {
          cplx a[4];
          a[0] = c; a[1] = cmul(c, z64); a[2] = cmul(a[1], z64); a[3] = cmul(a[2], z64);
#pragma unroll
          for (int i = 0; i < 8; i++) {
#pragma unroll
            for (int k = 0; k < 4; k++) {
              sts32(ta + (8 * k + i) * 128 + (l4 ^ (i << 4)), pack(a[k].x, -a[k].y));
              if (i < 7) a[k] = cmul(a[k], z8);
            }
          }
        }
        fence_async_smem();
        bar_sync(3);
        const uint64_t da = desc128(sm + TAB), db = desc128(sm + TAB + 16384);
        WG_FENCE();
#pragma unroll
        for (int ks = 0; ks < 8; ks++) wgmma_ss_n48<0, 0>(acc, da + (ks >> 2) * 512 + (ks & 3) * 2, db + (ks >> 2) * 384 + (ks & 3) * 2, ks ? 1 : (r & 1));
        WG_COMMIT();
        wg_wait<0>();
        pin<24>(acc);
        if (r & 1) {
          const int g = lane >> 2, tq = lane & 3;
          const uint32_t kc = sm + KC + ((r >> 1) * 2 + (w >> 1)) * 1408;
          float v[12];
#pragma unroll
          for (int i = 0; i < 12; i++) v[i] = (w >> 1) ? acc[12 + i] : acc[i];
          if ((tid & 63) == 0) v[0] += dsk[0];
#pragma unroll
          for (int h = 0; h < 2; h++) {
            const int b = 16 * (w & 1) + g + 8 * h;
            sts32(kc + (8 * b + 2 * tq) * 2, pack(v[2 * h], v[2 * h + 1]));
            sts32(kc + (tq < 2 ? 256 + 4 * b + 2 * tq : 256 + 64 * tq + 2 * b) * 2, pack(v[4 + 2 * h], v[5 + 2 * h]));
            const uint32_t t = pack(v[8 + 2 * h], v[9 + 2 * h]);
            if (tq < 3) { sts16(kc + (512 + 64 * tq + b) * 2, t); sts16(kc + (544 + 64 * tq + b) * 2, t >> 16); }
          }
        }
        PROFT(33 + r);
      }
      bar_sync(3);
      if (tid < 16) sts128(sm + TAB + (tid >> 2) * PSZ + (tid & 3) * 16, 0, 0, 0, 0);
#pragma unroll 1
      for (int i = 0; i < 4; i++) {
        const int L0 = 4 * (tid + 128 * i);
        uint32_t o[5];
#pragma unroll
        for (int j = 0; j < 5; j++) {
          const int l = L0 - 1 + j;
          const int rk = l < 128 ? max(l, 0) : (int)(pack((float)l, 0.f) - 0x4280u);
          o[j] = sm + KC + rk * 2;
        }
#pragma unroll
        for (int ch = 0; ch < 4; ch++) {
          uint32_t k[5];
#pragma unroll
          for (int j = 0; j < 5; j++) k[j] = lds16(o[j] + ch * 1408);
          if (L0 == 0) k[0] = 0;
          sts128(sm + TAB + ch * PSZ + (16 + L0) * 4, k[1] | (k[0] << 16), k[2] | (k[1] << 16), k[3] | (k[2] << 16), k[4] | (k[3] << 16));
        }
      }
      __syncwarp();
      if (lane == 0) mbar_arrive(bars + B_P * 8);
      PROFT(37);
    }
  } else {
    asm volatile("setmaxnreg.dec.sync.aligned.u32 24;");
    if (warp == 12) {
      if (elect()) {
        uint32_t st = sm;
#pragma unroll 1
        for (int kb = 3; kb < 8; kb++) {
          const uint32_t b = bars + (B_F1 + kb) * 8;
          mbar_wait(bars + (B_D1 + kb - 3) * 8);
          mbar_expect(b, 16384 + 2 * HT * 128);
          tma2d(st, &tm_wg, ft * 64, kb * 64, b);
          tma2d(st + 16384, &tm_x, kb * 64, tc * 2 * HT, b);
          tma2d(st + 8192, &tm_wu, ft * 64, kb * 64, b);
          tma2d(st + 16384 + G1_XB, &tm_x, kb * 64, tc * 2 * HT + HT, b);
          st += G1_STAGE;
          if (st == sm + AUX) st = sm;
        }
        if (mainc) {
          mbar_wait(bars + B_HST * 8);
          flag_wait(g_cnt + 64 + 32 * ((mt * 128) / HT), NFT);
          flag_wait(g_cnt + 64 + 32 * ((mt * 128 + 127) / HT), NFT);
          fence_async_all();
          PROFT(40);
          const uint4* src = g_h + mt * 128 * 8;
          uint32_t hs = sm + HRING;
#pragma unroll 1
          for (int kb = 0; kb < NFT; kb++) {
            if (kb == 4) mbar_wait(bars + B_CVD * 8);
            if (kb >= 7) mbar_wait(bars + (B_D2 + kb - 7) * 8);
            const uint32_t b = bars + (B_F2 + kb) * 8;
            mbar_expect(b, 16384);
            bulk_ld(hs, src, 16384, b);
            src += SEQ * 8;
            hs += 16384;
            if (hs == sm + WRING) hs = sm + HRING;
          }
        }
      }
    } else if (warp == 13) {
      if (mainc && elect()) {
        uint32_t ws = sm + WRING + 8192;
        mbar_wait(bars + (B_D1 + 5) * 8);
#pragma unroll 1
        for (int kb = 0; kb < NFT; kb++) {
          if (kb == 5) mbar_wait(bars + (B_D1 + 7) * 8);
          if (kb >= 6) mbar_wait(bars + (B_D2 + kb - 6) * 8);
          const uint32_t b = bars + (B_F2 + kb) * 8;
          mbar_expect(b, 8192);
          tma2d(ws, &tm_wd, dt * 64, kb * 64, b);
          ws += 8192;
          if (ws == sm + UOFF) ws = sm + WRING;
        }
      }
    } else if (warp == 14) {
      if (lt2 == 0 && lane < 13) g_cnt[32 + 32 * lane] = 0;
      __syncwarp();
      if (mainc) {
        mbar_wait(bars + B_LND * 8);
        if (lane == 0) flag_arrive(g_cnt);
      }
      PROFT(41);
      flag_wait(g_cnt, NMAIN);
      PROFT(42);
#pragma unroll 1
      for (int i = lane; i < 2 * 176; i += 32) {
        const int j = i >= 176 ? i - 176 + HT : i;
        sts32(sm + MEANS + i * 4, __float_as_uint(__ldcg(g_mean + min(tc * 2 * HT + j, SEQ - 1))));
      }
      if (mainc) {
        const float4 v = __ldcg((const float4*)(g_r2 + mt * 128) + lane);
        sts128(sm + R2S + lane * 16, __float_as_uint(v.x), __float_as_uint(v.y), __float_as_uint(v.z), __float_as_uint(v.w));
      }
      __syncwarp();
      if (lane == 0) {
        mbar_arrive(bars + B_STAT * 8);
        if (mainc) {
          fence_async_all();
          mbar_wait(bars + (B_D1 + 5) * 8);
          mbar_expect(bars + B_U * 8, 136 * 128);
          bulk_ld(sm + UOFF, g_u + lt2 * 136 * 8, 136 * 128, bars + B_U * 8);
          mbar_wait(bars + B_CVD * 8);
          mbar_expect(bars + B_X * 8, 16384);
          tma2d(sm + TAB, &tm_x2, dt * 64, mt * 128, bars + B_X * 8);
        }
        flag_arrive(g_cnt + 32);
        if (mainc) {
          PROFT(43);
          flag_wait(g_cnt + 32, NCTA);
          PROFT(44);
          fence_async_all();
          mbar_expect(bars + B_Y * 8, 16384);
          bulk_ld(sm + TAB + 16384, g_y + (mt * DM + dt * 64) * 32, 16384, bars + B_Y * 8);
          if (lt2 == 0) g_cnt[0] = 0;
        }
      }
    } else {
      if (elect()) {
        if (mainc) {
          asm volatile("cp.async.bulk.prefetch.L2.global [%0], %1;" ::"l"(p.wg + 192 * FF * 2 + lt2 * 6880), "r"(6880) : "memory");
          asm volatile("cp.async.bulk.prefetch.L2.global [%0], %1;" ::"l"(p.wu + 192 * FF * 2 + lt2 * 6880), "r"(6880) : "memory");
          asm volatile("cp.async.bulk.prefetch.L2.global [%0], %1;" ::"l"(p.wd + lt2 * 11008), "r"(11008) : "memory");
        }
#pragma unroll
        for (int wg = 0; wg < 2; wg++) {
          const int tok0 = (tc * 2 + wg) * HT;
          mbar_wait(bars + (B_STG + wg) * 8);
          asm volatile("cp.async.bulk.global.shared::cta.bulk_group [%0], [%1], %2;"
                       ::"l"(g_h + (ft * SEQ + tok0) * 8), "r"(sm + HRING + wg * G1_XB), "r"(min(HT, SEQ - tok0) * 128) : "memory");
          asm volatile("cp.async.bulk.commit_group;" ::: "memory");
        }
        asm volatile("cp.async.bulk.wait_group 0;" ::: "memory");
        PROFT(45);
        mbar_arrive(bars + B_HST * 8);
        fence_async_all();
        asm volatile("fence.acq_rel.gpu;" ::: "memory");
        asm volatile("red.relaxed.gpu.global.add.u32 [%0], 1;" ::"l"(g_cnt + 64 + 64 * tc) : "memory");
        asm volatile("red.relaxed.gpu.global.add.u32 [%0], 1;" ::"l"(g_cnt + 96 + 64 * tc) : "memory");
        PROFT(46);
      }
    }
  }
}

typedef CUresult (*EncodeFn)(CUtensorMap*, CUtensorMapDataType, cuuint32_t, void*, const cuuint64_t*, const cuuint64_t*, const cuuint32_t*,
                             const cuuint32_t*, CUtensorMapInterleave, CUtensorMapSwizzle, CUtensorMapL2promotion, CUtensorMapFloatOOBfill);

void make_map(EncodeFn enc, CUtensorMap* m, const void* base, uint64_t cols, uint64_t rows, uint32_t box_rows) {
  cuuint64_t dims[2] = {cols, rows}, strides[1] = {cols * 2};
  cuuint32_t box[2] = {64, box_rows}, es[2] = {1, 1};
  enc(m, CU_TENSOR_MAP_DATA_TYPE_BFLOAT16, 2, const_cast<void*>(base), dims, strides, box, es, CU_TENSOR_MAP_INTERLEAVE_NONE,
      CU_TENSOR_MAP_SWIZZLE_128B, CU_TENSOR_MAP_L2_PROMOTION_L2_128B, CU_TENSOR_MAP_FLOAT_OOB_FILL_NONE);
}

}

extern "C" void kernel_launch(void* const* d_in, const int* in_sizes, int n_in, void* d_out, int out_size) {
  static EncodeFn enc = nullptr;
  if (!enc) {
    void* fn = nullptr;
    cudaDriverEntryPointQueryResult q;
    cudaGetDriverEntryPoint("cuTensorMapEncodeTiled", &fn, cudaEnableDefault, &q);
    enc = (EncodeFn)fn;
    cudaFuncSetAttribute(fused_kernel, cudaFuncAttributeMaxDynamicSharedMemorySize, SMEM_BYTES);
  }
  CUtensorMap tx, twg, twu, twd, tx2, tout;
  make_map(enc, &tx, d_in[0], DM, SEQ, HT);
  make_map(enc, &twg, d_in[10], FF, DM, 64);
  make_map(enc, &twu, d_in[11], FF, DM, 64);
  make_map(enc, &twd, d_in[12], DM, FF, 64);
  make_map(enc, &tx2, d_in[0], DM, SEQ, 128);
  make_map(enc, &tout, d_out, DM, SEQ, 16);
  Params p;
  p.x = (const uint4*)d_in[0];
  p.are = (const uint32_t*)d_in[1]; p.aim = (const uint32_t*)d_in[2]; p.bre = (const uint32_t*)d_in[3];
  p.bim = (const uint32_t*)d_in[4]; p.cre = (const uint32_t*)d_in[5]; p.cim = (const uint32_t*)d_in[6];
  p.logdt = (const __nv_bfloat16*)d_in[7]; p.dskip = (const __nv_bfloat16*)d_in[8];
  p.wg = (const uint8_t*)d_in[10]; p.wu = (const uint8_t*)d_in[11]; p.wd = (const uint8_t*)d_in[12];
  fused_kernel<<<NCTA, 512, SMEM_BYTES, cudaStreamPerThread>>>(tx, twg, twu, twd, tx2, tout, p);
}
```

```cpp
#include <cuda_runtime.h>
#include <cuda_bf16.h>
#include <cuda.h>
#include <stdint.h>

namespace {

constexpr int SEQ = 2048, DM = 512, FF = 1376;
constexpr int NCTA = 132, NMAIN = 128;
constexpr int HT0 = 167, HT1 = 175, CT = HT0 + HT1;
constexpr int NCH = 4, HCH = 48;
constexpr int UP = 136;
constexpr int NFT = 22;

constexpr int G1_XB = 22528;
constexpr int G1_STAGE = 16384 + 2 * G1_XB;
constexpr int AUX = 3 * G1_STAGE;
constexpr int HRING = 0;
constexpr int WRING = 7 * 16384;
constexpr int UOFF = 163840;
constexpr int PSZ = 4992;
constexpr int PT = PSZ + 2048, WOFF = 2 * PT, RND = 2 * PT + 2 * 4096;
constexpr int TAB = AUX;
constexpr int XT = TAB + 22528, GT = HRING;
constexpr int KTAB = 2 * G1_STAGE, KSL = 13312;
constexpr int KC = AUX + 2 * RND - 5632;
constexpr int KRAW = TAB + WOFF;
constexpr int MEANS = KC + 4 * 1408;
constexpr int R2S = MEANS + 1408;
constexpr int LNP = R2S + 512;
constexpr int BARS = LNP + 512;
constexpr int B_FA = 0, B_FB = 8, B_STAT = 16, B_U = 17, B_HST = 18, B_X = 19, B_F2 = 20, B_P = 42, B_LND = 43,
              B_W = 44, B_D2 = 45, B_STG = 66, B_D1 = B_STG + 2 * NCH, B_KD = B_D1 + 8, B_CV1 = B_KD + 1, B_CVD = B_KD + 2, B_TD = B_KD + 3, NBAR = B_KD + 4;
constexpr int SMEM_BYTES = BARS + NBAR * 8;
static_assert(SMEM_BYTES <= 232448, "smem");
static_assert(XT % 1024 == 0 && XT >= TAB + RND && XT + 16384 <= TAB + 2 * RND && KC >= TAB + RND + WOFF && PT % 128 == 0, "tiles");
static_assert(KTAB + 8 * KSL <= R2S && KTAB % 1024 == 0, "tables");

__device__ uint4 g_h[NFT * SEQ * 8];
__device__ uint4 g_u[NMAIN * UP * 8];
__device__ float4 g_stat[(12 * 176 + SEQ) / 4];
__device__ unsigned g_cnt[18 * 32];

struct Params {
  const uint16_t* logdt;
  const uint32_t* ssm[6];
  const uint16_t* dskip;
  const uint4* x;
  uint64_t d128, dq[3];
  uint4 *h, *u, *out;
  float* stat;
  unsigned* cnt;
  const uint8_t *wg, *wu, *wd;
  uint32_t role[NCTA];
};

template <int TA, int TB>
__device__ __forceinline__ void wgmma_ss_n176(float* d, uint64_t da, uint64_t db, int sc) {
  asm volatile("{\n.reg .pred p;\nsetp.ne.b32 p, %90, 0;\n"
      "wgmma.mma_async.sync.aligned.m64n176k16.f32.bf16.bf16 {"
      "%0, %1, %2, %3, %4, %5, %6, %7, %8, %9, %10, %11, %12, %13, %14, %15,"
      "%16, %17, %18, %19, %20, %21, %22, %23, %24, %25, %26, %27, %28, %29, %30, %31,"
      "%32, %33, %34, %35, %36, %37, %38, %39, %40, %41, %42, %43, %44, %45, %46, %47,"
      "%48, %49, %50, %51, %52, %53, %54, %55, %56, %57, %58, %59, %60, %61, %62, %63,"
      "%64, %65, %66, %67, %68, %69, %70, %71, %72, %73, %74, %75, %76, %77, %78, %79,"
      "%80, %81, %82, %83, %84, %85, %86, %87"
      "}, %88, %89, p, 1, 1, %91, %92;\n}\n"
    : "+f"(d[0]), "+f"(d[1]), "+f"(d[2]), "+f"(d[3]), "+f"(d[4]), "+f"(d[5]), "+f"(d[6]), "+f"(d[7]),
      "+f"(d[8]), "+f"(d[9]), "+f"(d[10]), "+f"(d[11]), "+f"(d[12]), "+f"(d[13]), "+f"(d[14]), "+f"(d[15]),
      "+f"(d[16]), "+f"(d[17]), "+f"(d[18]), "+f"(d[19]), "+f"(d[20]), "+f"(d[21]), "+f"(d[22]), "+f"(d[23]),
      "+f"(d[24]), "+f"(d[25]), "+f"(d[26]), "+f"(d[27]), "+f"(d[28]), "+f"(d[29]), "+f"(d[30]), "+f"(d[31]),
      "+f"(d[32]), "+f"(d[33]), "+f"(d[34]), "+f"(d[35]), "+f"(d[36]), "+f"(d[37]), "+f"(d[38]), "+f"(d[39]),
      "+f"(d[40]), "+f"(d[41]), "+f"(d[42]), "+f"(d[43]), "+f"(d[44]), "+f"(d[45]), "+f"(d[46]), "+f"(d[47]),
      "+f"(d[48]), "+f"(d[49]), "+f"(d[50]), "+f"(d[51]), "+f"(d[52]), "+f"(d[53]), "+f"(d[54]), "+f"(d[55]),
      "+f"(d[56]), "+f"(d[57]), "+f"(d[58]), "+f"(d[59]), "+f"(d[60]), "+f"(d[61]), "+f"(d[62]), "+f"(d[63]),
      "+f"(d[64]), "+f"(d[65]), "+f"(d[66]), "+f"(d[67]), "+f"(d[68]), "+f"(d[69]), "+f"(d[70]), "+f"(d[71]),
      "+f"(d[72]), "+f"(d[73]), "+f"(d[74]), "+f"(d[75]), "+f"(d[76]), "+f"(d[77]), "+f"(d[78]), "+f"(d[79]),
      "+f"(d[80]), "+f"(d[81]), "+f"(d[82]), "+f"(d[83]), "+f"(d[84]), "+f"(d[85]), "+f"(d[86]), "+f"(d[87])
    : "l"(da), "l"(db), "r"(sc), "n"(TA), "n"(TB));
}
template <int TA, int TB>
__device__ __forceinline__ void wgmma_ss_n168(float* d, uint64_t da, uint64_t db, int sc) {
  asm volatile("{\n.reg .pred p;\nsetp.ne.b32 p, %86, 0;\n"
      "wgmma.mma_async.sync.aligned.m64n168k16.f32.bf16.bf16 {"
      "%0, %1, %2, %3, %4, %5, %6, %7, %8, %9, %10, %11, %12, %13, %14, %15,"
      "%16, %17, %18, %19, %20, %21, %22, %23, %24, %25, %26, %27, %28, %29, %30, %31,"
      "%32, %33, %34, %35, %36, %37, %38, %39, %40, %41, %42, %43, %44, %45, %46, %47,"
      "%48, %49, %50, %51, %52, %53, %54, %55, %56, %57, %58, %59, %60, %61, %62, %63,"
      "%64, %65, %66, %67, %68, %69, %70, %71, %72, %73, %74, %75, %76, %77, %78, %79,"
      "%80, %81, %82, %83"
      "}, %84, %85, p, 1, 1, %87, %88;\n}\n"
    : "+f"(d[0]), "+f"(d[1]), "+f"(d[2]), "+f"(d[3]), "+f"(d[4]), "+f"(d[5]), "+f"(d[6]), "+f"(d[7]),
      "+f"(d[8]), "+f"(d[9]), "+f"(d[10]), "+f"(d[11]), "+f"(d[12]), "+f"(d[13]), "+f"(d[14]), "+f"(d[15]),
      "+f"(d[16]), "+f"(d[17]), "+f"(d[18]), "+f"(d[19]), "+f"(d[20]), "+f"(d[21]), "+f"(d[22]), "+f"(d[23]),
      "+f"(d[24]), "+f"(d[25]), "+f"(d[26]), "+f"(d[27]), "+f"(d[28]), "+f"(d[29]), "+f"(d[30]), "+f"(d[31]),
      "+f"(d[32]), "+f"(d[33]), "+f"(d[34]), "+f"(d[35]), "+f"(d[36]), "+f"(d[37]), "+f"(d[38]), "+f"(d[39]),
      "+f"(d[40]), "+f"(d[41]), "+f"(d[42]), "+f"(d[43]), "+f"(d[44]), "+f"(d[45]), "+f"(d[46]), "+f"(d[47]),
      "+f"(d[48]), "+f"(d[49]), "+f"(d[50]), "+f"(d[51]), "+f"(d[52]), "+f"(d[53]), "+f"(d[54]), "+f"(d[55]),
      "+f"(d[56]), "+f"(d[57]), "+f"(d[58]), "+f"(d[59]), "+f"(d[60]), "+f"(d[61]), "+f"(d[62]), "+f"(d[63]),
      "+f"(d[64]), "+f"(d[65]), "+f"(d[66]), "+f"(d[67]), "+f"(d[68]), "+f"(d[69]), "+f"(d[70]), "+f"(d[71]),
      "+f"(d[72]), "+f"(d[73]), "+f"(d[74]), "+f"(d[75]), "+f"(d[76]), "+f"(d[77]), "+f"(d[78]), "+f"(d[79]),
      "+f"(d[80]), "+f"(d[81]), "+f"(d[82]), "+f"(d[83])
    : "l"(da), "l"(db), "r"(sc), "n"(TA), "n"(TB));
}
template <int TA, int TB>
__device__ __forceinline__ void wgmma_ss_n128(float* d, uint64_t da, uint64_t db, int sc) {
  asm volatile("{\n.reg .pred p;\nsetp.ne.b32 p, %66, 0;\n"
      "wgmma.mma_async.sync.aligned.m64n128k16.f32.bf16.bf16 {"
      "%0, %1, %2, %3, %4, %5, %6, %7, %8, %9, %10, %11, %12, %13, %14, %15,"
      "%16, %17, %18, %19, %20, %21, %22, %23, %24, %25, %26, %27, %28, %29, %30, %31,"
      "%32, %33, %34, %35, %36, %37, %38, %39, %40, %41, %42, %43, %44, %45, %46, %47,"
      "%48, %49, %50, %51, %52, %53, %54, %55, %56, %57, %58, %59, %60, %61, %62, %63"
      "}, %64, %65, p, 1, 1, %67, %68;\n}\n"
    : "+f"(d[0]), "+f"(d[1]), "+f"(d[2]), "+f"(d[3]), "+f"(d[4]), "+f"(d[5]), "+f"(d[6]), "+f"(d[7]),
      "+f"(d[8]), "+f"(d[9]), "+f"(d[10]), "+f"(d[11]), "+f"(d[12]), "+f"(d[13]), "+f"(d[14]), "+f"(d[15]),
      "+f"(d[16]), "+f"(d[17]), "+f"(d[18]), "+f"(d[19]), "+f"(d[20]), "+f"(d[21]), "+f"(d[22]), "+f"(d[23]),
      "+f"(d[24]), "+f"(d[25]), "+f"(d[26]), "+f"(d[27]), "+f"(d[28]), "+f"(d[29]), "+f"(d[30]), "+f"(d[31]),
      "+f"(d[32]), "+f"(d[33]), "+f"(d[34]), "+f"(d[35]), "+f"(d[36]), "+f"(d[37]), "+f"(d[38]), "+f"(d[39]),
      "+f"(d[40]), "+f"(d[41]), "+f"(d[42]), "+f"(d[43]), "+f"(d[44]), "+f"(d[45]), "+f"(d[46]), "+f"(d[47]),
      "+f"(d[48]), "+f"(d[49]), "+f"(d[50]), "+f"(d[51]), "+f"(d[52]), "+f"(d[53]), "+f"(d[54]), "+f"(d[55]),
      "+f"(d[56]), "+f"(d[57]), "+f"(d[58]), "+f"(d[59]), "+f"(d[60]), "+f"(d[61]), "+f"(d[62]), "+f"(d[63])
    : "l"(da), "l"(db), "r"(sc), "n"(TA), "n"(TB));
}
template <int TA, int TB>
__device__ __forceinline__ void wgmma_ss_n40_f16(float* d, uint64_t da, uint64_t db, int sc) {
  asm volatile("{\n.reg .pred p;\nsetp.ne.b32 p, %22, 0;\n"
      "wgmma.mma_async.sync.aligned.m64n40k16.f32.f16.f16 {"
      "%0, %1, %2, %3, %4, %5, %6, %7, %8, %9, %10, %11, %12, %13, %14, %15,"
      "%16, %17, %18, %19"
      "}, %20, %21, p, 1, 1, %23, %24;\n}\n"
    : "+f"(d[0]), "+f"(d[1]), "+f"(d[2]), "+f"(d[3]), "+f"(d[4]), "+f"(d[5]), "+f"(d[6]), "+f"(d[7]),
      "+f"(d[8]), "+f"(d[9]), "+f"(d[10]), "+f"(d[11]), "+f"(d[12]), "+f"(d[13]), "+f"(d[14]), "+f"(d[15]),
      "+f"(d[16]), "+f"(d[17]), "+f"(d[18]), "+f"(d[19])
    : "l"(da), "l"(db), "r"(sc), "n"(TA), "n"(TB));
}
template <int TB>
__device__ __forceinline__ void wgmma_rs_n32(float* d, uint32_t a0, uint32_t a1, uint32_t a2, uint32_t a3, uint64_t db, int sc) {
  asm volatile("{\n.reg .pred p;\nsetp.ne.b32 p, %21, 0;\n"
      "wgmma.mma_async.sync.aligned.m64n32k16.f32.bf16.bf16 {"
      "%0, %1, %2, %3, %4, %5, %6, %7, %8, %9, %10, %11, %12, %13, %14, %15"
      "}, {%16,%17,%18,%19}, %20, p, 1, 1, %22;\n}\n"
    : "+f"(d[0]), "+f"(d[1]), "+f"(d[2]), "+f"(d[3]), "+f"(d[4]), "+f"(d[5]), "+f"(d[6]), "+f"(d[7]),
      "+f"(d[8]), "+f"(d[9]), "+f"(d[10]), "+f"(d[11]), "+f"(d[12]), "+f"(d[13]), "+f"(d[14]), "+f"(d[15])
    : "r"(a0), "r"(a1), "r"(a2), "r"(a3), "l"(db), "r"(sc), "n"(TB));
}
#define WG_FENCE() asm volatile("wgmma.fence.sync.aligned;" ::: "memory")
#define WG_COMMIT() asm volatile("wgmma.commit_group.sync.aligned;" ::: "memory")
template <int N> __device__ __forceinline__ void wg_wait() { asm volatile("wgmma.wait_group.sync.aligned %0;" ::"n"(N) : "memory"); }
template <int N> __device__ __forceinline__ void pin(float* a) {
#pragma unroll
  for (int i = 0; i < N; i++) asm volatile("" : "+f"(a[i])::"memory");
}
constexpr uint64_t D128 = 0x4000004000010000ull;

__device__ __forceinline__ void mbar_init(uint32_t bar, uint32_t cnt) { asm volatile("mbarrier.init.shared::cta.b64 [%0], %1;" ::"r"(bar), "r"(cnt) : "memory"); }
__device__ __forceinline__ void mbar_arrive(uint32_t bar) { asm volatile("mbarrier.arrive.shared::cta.b64 _, [%0];" ::"r"(bar) : "memory"); }
__device__ __forceinline__ void mbar_expect(uint32_t bar, uint32_t bytes) { asm volatile("mbarrier.arrive.expect_tx.shared::cta.b64 _, [%0], %1;" ::"r"(bar), "r"(bytes) : "memory"); }
__device__ __forceinline__ void mbar_wait(uint32_t bar) {
  asm volatile(
      "{\n.reg .pred p;\n.reg .u32 c;\nmov.u32 c, 0;\n"
      "W_%=:\nmbarrier.try_wait.parity.shared::cta.b64 p, [%0], 0;\n@p bra D_%=;\n"
      "add.u32 c, c, 1;\nsetp.lt.u32 p, c, 0x40000;\n@p bra W_%=;\ntrap;\nD_%=:\n}\n" ::"r"(bar) : "memory");
}
__device__ __forceinline__ void flag_wait(const unsigned* p, unsigned target) {
  asm volatile(
      "{\n.reg .pred p;\n.reg .u32 c, v;\nmov.u32 c, 0;\n"
      "W_%=:\nld.relaxed.gpu.global.u32 v, [%0];\nsetp.ge.u32 p, v, %1;\n@p bra D_%=;\n"
      "add.u32 c, c, 1;\nsetp.lt.u32 p, c, 0x100000;\n@p bra W_%=;\ntrap;\nD_%=:\nfence.acquire.gpu;\n}\n" ::"l"(p), "r"(target) : "memory");
}
__device__ __forceinline__ void flag_arrive(unsigned* p) { asm volatile("red.release.gpu.global.add.u32 [%0], 1;" ::"l"(p) : "memory"); }
__device__ __forceinline__ void fence_async_smem() { asm volatile("fence.proxy.async.shared::cta;" ::: "memory"); }
__device__ __forceinline__ void fence_async_gmem() { asm volatile("fence.proxy.async.global;" ::: "memory"); }
__device__ __forceinline__ void bar_sync(int id) { asm volatile("bar.sync %0, 128;" ::"r"(id) : "memory"); }
__device__ __forceinline__ bool elect() {
  uint32_t e;
  asm volatile("{\n.reg .pred p;\nelect.sync _|p, 0xffffffff;\nselp.u32 %0, 1, 0, p;\n}\n" : "=r"(e));
  return e;
}
__device__ __forceinline__ void warp_arrive(uint32_t bar) {
  __syncwarp();
  if (elect()) mbar_arrive(bar);
}
__device__ __forceinline__ void tma2d(uint32_t dst, const CUtensorMap* tm, int c0, int c1, uint32_t bar) {
  asm volatile("cp.async.bulk.tensor.2d.shared::cluster.global.mbarrier::complete_tx::bytes [%0], [%1, {%3, %4}], [%2];"
               ::"r"(dst), "l"(tm), "r"(bar), "r"(c0), "r"(c1) : "memory");
}
__device__ __forceinline__ void bulk_ld(uint32_t dst, const void* src, uint32_t bytes, uint32_t bar) {
  asm volatile("cp.async.bulk.shared::cluster.global.mbarrier::complete_tx::bytes [%0], [%1], %2, [%3];"
               ::"r"(dst), "l"(src), "r"(bytes), "r"(bar) : "memory");
}
__device__ __forceinline__ void l2_prefetch(const void* src, uint32_t bytes) {
  asm volatile("cp.async.bulk.prefetch.L2.global [%0], %1;" ::"l"(src), "r"(bytes) : "memory");
}
__device__ __forceinline__ uint32_t lds32(uint32_t a) { uint32_t v; asm volatile("ld.shared.u32 %0, [%1];" : "=r"(v) : "r"(a)); return v; }
__device__ __forceinline__ void lds128f(float* v, uint32_t a) {
  asm volatile("ld.shared.v4.f32 {%0,%1,%2,%3}, [%4];" : "=f"(v[0]), "=f"(v[1]), "=f"(v[2]), "=f"(v[3]) : "r"(a) : "memory");
}
__device__ __forceinline__ void lds128(uint32_t* v, uint32_t a) {
  asm volatile("ld.shared.v4.u32 {%0,%1,%2,%3}, [%4];" : "=r"(v[0]), "=r"(v[1]), "=r"(v[2]), "=r"(v[3]) : "r"(a) : "memory");
}
__device__ __forceinline__ void sts32(uint32_t a, uint32_t v) { asm volatile("st.shared.u32 [%0], %1;" ::"r"(a), "r"(v) : "memory"); }
__device__ __forceinline__ void sts16(uint32_t a, uint32_t v) { asm volatile("st.shared.u16 [%0], %1;" ::"r"(a), "h"((uint16_t)v) : "memory"); }
__device__ __forceinline__ void sts128(uint32_t a, uint32_t x, uint32_t y, uint32_t z, uint32_t w) {
  asm volatile("st.shared.v4.u32 [%0], {%1,%2,%3,%4};" ::"r"(a), "r"(x), "r"(y), "r"(z), "r"(w) : "memory");
}
__device__ __forceinline__ void sts128f(uint32_t a, float x, float y, float z, float w) {
  asm volatile("st.shared.v4.f32 [%0], {%1,%2,%3,%4};" ::"r"(a), "f"(x), "f"(y), "f"(z), "f"(w) : "memory");
}
__device__ __forceinline__ uint32_t pack(float lo, float hi) { uint32_t r; asm("cvt.rn.bf16x2.f32 %0, %1, %2;" : "=r"(r) : "f"(hi), "f"(lo)); return r; }
__device__ __forceinline__ float blo(uint32_t v) { return __uint_as_float(v << 16); }
__device__ __forceinline__ float bhi(uint32_t v) { return __uint_as_float(v & 0xffff0000u); }
__device__ __forceinline__ float rbf(float v) { return __uint_as_float(pack(0.f, v)); }
__device__ __forceinline__ uint32_t badd2(uint32_t a, uint32_t b) { uint32_t r; asm("add.rn.bf16x2 %0, %1, %2;" : "=r"(r) : "r"(a), "r"(b)); return r; }
__device__ __forceinline__ uint32_t bfma2(uint32_t a, uint32_t b, uint32_t c) { uint32_t r; asm("fma.rn.bf16x2 %0, %1, %2, %3;" : "=r"(r) : "r"(a), "r"(b), "r"(c)); return r; }
__device__ __forceinline__ uint32_t norm2(uint32_t x, uint32_t m, uint32_t ih, uint32_t il) {
  uint32_t c, t;
  asm("sub.rn.bf16x2 %0, %1, %2;" : "=r"(c) : "r"(x), "r"(m));
  asm("mul.rn.bf16x2 %0, %1, %2;" : "=r"(t) : "r"(c), "r"(il));
  asm("fma.rn.bf16x2 %0, %1, %2, %3;" : "=r"(t) : "r"(c), "r"(ih), "r"(t));
  return t;
}
struct cplx { float x, y; };
__device__ __forceinline__ cplx cmul(cplx a, cplx b) { return {fmaf(a.x, b.x, -a.y * b.y), fmaf(a.x, b.y, a.y * b.x)}; }
__device__ __forceinline__ cplx cmulc(cplx a, cplx b) { return {fmaf(a.x, b.x, a.y * b.y), fmaf(a.y, b.x, -a.x * b.y)}; }
__device__ __forceinline__ cplx csq(cplx a) { return {fmaf(a.x, a.x, -a.y * a.y), (a.x * a.y) * 2.f}; }
struct cplxh { uint32_t x, y; };
__device__ __forceinline__ uint32_t packh(float lo, float hi) { uint32_t r; asm("cvt.rn.f16x2.f32 %0, %1, %2;" : "=r"(r) : "f"(hi), "f"(lo)); return r; }
__device__ __forceinline__ cplxh toh(cplx a, cplx b) { return {packh(a.x, b.x), packh(a.y, b.y)}; }
__device__ __forceinline__ cplxh hmul(cplxh a, cplxh b) {
  cplxh r;
  asm("{\n.reg .b32 t, u;\nmul.rn.f16x2 t, %3, %5;\nneg.f16x2 t, t;\nfma.rn.f16x2 %0, %2, %4, t;\nmul.rn.f16x2 u, %3, %4;\nfma.rn.f16x2 %1, %2, %5, u;\n}\n"
      : "=&r"(r.x), "=r"(r.y) : "r"(a.x), "r"(a.y), "r"(b.x), "r"(b.y));
  return r;
}
__device__ __forceinline__ cplxh hmulc(cplxh a, cplxh b) {
  cplxh r;
  asm("{\n.reg .b32 t, u;\nmul.rn.f16x2 t, %3, %5;\nfma.rn.f16x2 %0, %2, %4, t;\nmul.rn.f16x2 u, %2, %5;\nneg.f16x2 u, u;\nfma.rn.f16x2 %1, %3, %4, u;\n}\n"
      : "=&r"(r.x), "=r"(r.y) : "r"(a.x), "r"(a.y), "r"(b.x), "r"(b.y));
  return r;
}
__device__ __forceinline__ void stc(uint32_t a, cplxh v) { sts32(a, v.x); sts32(a + KSL, v.y); }
#define CH_ONE (cplxh{0x3C003C00u, 0u})
__device__ __forceinline__ uint32_t max_exp(uint32_t a, uint32_t b, uint32_t c, uint32_t d) {
  const uint32_t m = 0x7f807f80u;
  const uint32_t v = __vmaxu2(__vmaxu2(a & m, b & m), __vmaxu2(c & m, d & m));
  return min(max(__reduce_max_sync(0xffffffffu, max(v >> 16, v & 0xffffu)) >> 7, 8u), 253u);
}
__device__ __forceinline__ cplx cexp2(float al, float th) {
  float m;
  asm("ex2.approx.ftz.f32 %0, %1;" : "=f"(m) : "f"(al));
  const float ph = (th - rintf(th)) * 6.283185307179586f;
  return {m * __cosf(ph), m * __sinf(ph)};
}

template <bool NARROW> __device__ __forceinline__ void g1_steps(float* ag, float* au, uint64_t da, uint64_t db, int acc) {
#pragma unroll
  for (int ks = 0; ks < 4; ks++) {
    if (NARROW) {
      wgmma_ss_n168<1, 0>(ag, da + ks * 128, db + ks * 2, ks ? 1 : acc);
      wgmma_ss_n168<1, 0>(au, da + (512 + ks * 128), db + ks * 2, ks ? 1 : acc);
    } else {
      wgmma_ss_n176<1, 0>(ag, da + ks * 128, db + ks * 2, ks ? 1 : acc);
      wgmma_ss_n176<1, 0>(au, da + (512 + ks * 128), db + ks * 2, ks ? 1 : acc);
    }
  }
}
template <int Q> __device__ __forceinline__ void conv_loadA(uint32_t* R, uint32_t pa, uint32_t zero) {
  R[2] = lds32(pa + (608 * Q) * 4);
#pragma unroll
  for (int s = 0; s < 8; s++) {
    R[4 * s] = lds32(pa + (608 * Q + 16 * s + 8) * 4);
    R[4 * s + 1] = lds32(pa + (608 * Q + 16 * s + 16) * 4);
  }
#pragma unroll
  for (int s = 0; s < 8; s++) {
    asm volatile("or.b32 %0, %1, %2;" : "=r"(R[4 * s + 3]) : "r"(R[4 * s]), "r"(zero));
    if (s < 7) asm volatile("or.b32 %0, %1, %2;" : "=r"(R[4 * s + 6]) : "r"(R[4 * s + 1]), "r"(zero));
  }
}
template <int Q, int S0, int S1> __device__ __forceinline__ void conv_mma(float (*acc)[16], const uint32_t* R, uint64_t db) {
#pragma unroll
  for (int s = S0; s < S1; s++) {
#pragma unroll
    for (int B = Q; B < 4; B++)
      wgmma_rs_n32<0>(acc[B], R[4 * s], R[4 * s + 1], R[4 * s + 2], R[4 * s + 3], db + (8 + 32 * (B - Q) - s) * 8, (Q == 0 && s == 0) ? 0 : 1);
  }
}
template <int Q, int B> __device__ __forceinline__ void conv_mma_blk(float (*acc)[16], const uint32_t* R, uint64_t db) {
#pragma unroll
  for (int s = 0; s < 8; s++) wgmma_rs_n32<0>(acc[B], R[4 * s], R[4 * s + 1], R[4 * s + 2], R[4 * s + 3], db + (8 + 32 * (B - Q) - s) * 8, 1);
}
template <int B> __device__ __forceinline__ void conv_red(float (*acc)[16], uint32_t* prev, int lane, uint2* yo) {
  pin<16>(acc[B]);
  float* a = acc[B];
  uint32_t p0, p1;
  uint32_t v[6];
#pragma unroll
  for (int r = 1; r < 4; r++) {
#pragma unroll
    for (int i = 0; i < 2; i++) {
      const uint32_t pk = pack(a[4 * r + i], a[4 * r + i + 2]);
      v[2 * r - 2 + i] = __shfl_sync(0xffffffffu, lane < 32 - 8 * r ? pk : (B ? prev[2 * r - 2 + i] : 0u), lane - 8 * r);
      prev[2 * r - 2 + i] = pk;
    }
  }
  p0 = badd2(badd2(pack(a[0], a[2]), v[0]), badd2(v[2], v[4]));
  p1 = badd2(badd2(pack(a[1], a[3]), v[1]), badd2(v[3], v[5]));
  asm volatile("st.relaxed.gpu.global.v2.u32 [%0], {%1,%2};" ::"l"(yo + B * 4 * DM * 32), "r"(p0), "r"(p1) : "memory");
}

__device__ __forceinline__ void y_poll(uint32_t* y, const uint2* src) {
  asm volatile(
      "{\n.reg .pred q;\n.reg .u32 m, c;\nmov.u32 c, 0;\nP_%=:\n"
      "ld.relaxed.gpu.global.v2.u32 {%0,%8}, [%16+0];\nld.relaxed.gpu.global.v2.u32 {%1,%9}, [%16+2048];\n"
      "ld.relaxed.gpu.global.v2.u32 {%2,%10}, [%16+4096];\nld.relaxed.gpu.global.v2.u32 {%3,%11}, [%16+6144];\n"
      "ld.relaxed.gpu.global.v2.u32 {%4,%12}, [%16+8192];\nld.relaxed.gpu.global.v2.u32 {%5,%13}, [%16+10240];\n"
      "ld.relaxed.gpu.global.v2.u32 {%6,%14}, [%16+12288];\nld.relaxed.gpu.global.v2.u32 {%7,%15}, [%16+14336];\n"
      "max.u32 m, %0, %1;\nmax.u32 m, m, %2;\nmax.u32 m, m, %3;\nmax.u32 m, m, %4;\nmax.u32 m, m, %5;\nmax.u32 m, m, %6;\nmax.u32 m, m, %7;\nmax.u32 m, m, %8;\n"
      "max.u32 m, m, %9;\nmax.u32 m, m, %10;\nmax.u32 m, m, %11;\nmax.u32 m, m, %12;\nmax.u32 m, m, %13;\nmax.u32 m, m, %14;\nmax.u32 m, m, %15;\n"
      "setp.eq.u32 q, m, 0xffffffff;\nvote.sync.any.pred q, q, 0xffffffff;\n@!q bra Q_%=;\n"
      "add.u32 c, c, 1;\nsetp.lt.u32 q, c, 0x40000;\n@q bra P_%=;\ntrap;\nQ_%=:\n}\n"
      : "=&r"(y[0]), "=&r"(y[1]), "=&r"(y[2]), "=&r"(y[3]), "=&r"(y[4]), "=&r"(y[5]), "=&r"(y[6]), "=&r"(y[7]),
        "=&r"(y[8]), "=&r"(y[9]), "=&r"(y[10]), "=&r"(y[11]), "=&r"(y[12]), "=&r"(y[13]), "=&r"(y[14]), "=&r"(y[15])
      : "l"(src) : "memory");
}

template <bool BY_SM>
__global__ void __launch_bounds__(512, 1)
fused_kernel(const __grid_constant__ Params p, const __grid_constant__ CUtensorMap tm_x, const __grid_constant__ CUtensorMap tm_x1, const __grid_constant__ CUtensorMap tm_wg,
             const __grid_constant__ CUtensorMap tm_wu, const __grid_constant__ CUtensorMap tm_wd, const __grid_constant__ CUtensorMap tm_x2) {
  extern __shared__ __align__(1024) uint8_t smem_raw[];
  constexpr uint32_t sm = 1024;
  constexpr uint32_t bars = sm + BARS;
  int id = blockIdx.x;
  if (BY_SM) asm volatile("mov.u32 %0, %%smid;" : "=r"(id));
  const int lt2 = id < 120 ? id : id < 124 ? id + 8 : id - 4;
  const bool mainc = lt2 < NMAIN;
  uint32_t prm[10], ldt, dsk;
  if (threadIdx.x < 256) {
    const uint32_t o = ((lt2 & 127) * 256 + threadIdx.x) * 4, d2 = (o >> 7) & ~1u;
#define LDP(ty, dst, base, off) asm volatile("ld.global.nc." ty " %0, [%1];" : "=r"(dst) : "l"((const char*)(base) + (off)))
    LDP("u16", ldt, p.logdt, d2);
#pragma unroll
    for (int i = 0; i < 6; i++) LDP("u32", prm[i], p.ssm[i], o);
#pragma unroll
    for (int i = 2; i < 6; i++) LDP("u32", prm[4 + i], p.ssm[i], o ^ 128);
    LDP("u16", dsk, p.dskip, d2);
#undef LDP
  }
  const int warp = __shfl_sync(0xffffffffu, threadIdx.x >> 5, 0);
  const int lane = threadIdx.x & 31;
  const uint32_t role = p.role[id];
  const int ft = role & 255, tc = (role >> 8) & 255, mt = (role >> 16) & 255, dt = role >> 24;

  if (warp >= 12) {
    asm volatile("setmaxnreg.dec.sync.aligned.u32 24;");
    if (warp == 12) {
      if (elect()) {
        mbar_init(bars + B_FA * 8, 1);
        mbar_init(bars + B_FB * 8, 1);
        mbar_init(bars + (B_FA + 1) * 8, 1);
        mbar_init(bars + (B_FB + 1) * 8, 1);
        asm volatile("fence.mbarrier_init.release.cluster;" ::: "memory");
        mbar_expect(bars + B_FA * 8, 16384 + HT0 * 128);
        tma2d(sm, &tm_wg, ft * 64, 0, bars + B_FA * 8);
        tma2d(sm + 16384, &tm_x, 0, tc * CT, bars + B_FA * 8);
        tma2d(sm + 8192, &tm_wu, ft * 64, 0, bars + B_FA * 8);
        mbar_expect(bars + B_FB * 8, HT1 * 128);
        tma2d(sm + 16384 + G1_XB, &tm_x1, 0, tc * CT + HT0, bars + B_FB * 8);
        mbar_expect(bars + (B_FA + 1) * 8, 16384 + HT0 * 128);
        tma2d(sm + G1_STAGE, &tm_wg, ft * 64, 64, bars + (B_FA + 1) * 8);
        tma2d(sm + G1_STAGE + 16384, &tm_x, 64, tc * CT, bars + (B_FA + 1) * 8);
        tma2d(sm + G1_STAGE + 8192, &tm_wu, ft * 64, 64, bars + (B_FA + 1) * 8);
        mbar_expect(bars + (B_FB + 1) * 8, HT1 * 128);
        tma2d(sm + G1_STAGE + 16384 + G1_XB, &tm_x1, 64, tc * CT + HT0, bars + (B_FB + 1) * 8);
      }
    } else if (elect()) {
      if (warp == 13) {
#pragma unroll
        for (int i = 2; i < B_F2; i++) if (i != B_FB && i != B_FB + 1) mbar_init(bars + i * 8, 1);
#pragma unroll
        for (int i = B_D1; i < NBAR; i++) mbar_init(bars + i * 8, 8);
      } else if (warp == 14) {
#pragma unroll
        for (int i = B_F2; i < B_P; i++) mbar_init(bars + i * 8, 2);
        if (mainc) {
          l2_prefetch(p.x + lt2 * 1024, 16384);
          l2_prefetch(p.wg + 128 * FF * 2 + lt2 * 8256, 8256);
          l2_prefetch(p.wu + 128 * FF * 2 + lt2 * 8256, 8256);
        }
        uint32_t nsm;
        asm volatile("mov.u32 %0, %%nsmid;" : "=r"(nsm));
        if ((uint32_t)__cvta_generic_to_shared(smem_raw) != sm || (BY_SM && nsm != NCTA)) asm volatile("trap;");
      } else {
#pragma unroll
        for (int i = B_P; i < B_D1; i++) mbar_init(bars + i * 8, 4);
      }
    }
    __syncwarp();
    fence_async_smem();
    asm volatile("bar.arrive 6, 384;" ::: "memory");
    asm volatile("bar.arrive 7, 384;" ::: "memory");
    asm volatile("bar.sync 5, 256;" ::: "memory");
    if (!(warp & 1)) {
      if (mainc) mbar_wait(bars + B_TD * 8);
      if (warp == 12) {
        sts32(sm + 2 * G1_STAGE + 16384 + 167 * 128 + lane * 4, 0x3F803F80u);
        sts32(sm + 2 * G1_STAGE + 16384 + G1_XB + 175 * 128 + lane * 4, 0x3F803F80u);
      } else {
        sts128(sm + MEANS + lane * 16, ~0u, ~0u, ~0u, ~0u);
        sts128(sm + MEANS + 512 + lane * 16, ~0u, ~0u, ~0u, ~0u);
      }
      fence_async_smem();
      __syncwarp();
    }
    if (elect()) {
      if (warp == 12) {
        uint32_t st = sm + 2 * G1_STAGE;
#pragma unroll 1
        for (int kb = 2; kb < 8; kb++) {
          const uint32_t b = bars + (B_FA + kb) * 8;
          if (kb >= 3) mbar_wait(bars + (B_D1 + kb - 3) * 8);
          mbar_expect(b, 16384 + HT0 * 128);
          tma2d(st, &tm_wg, ft * 64, kb * 64, b);
          tma2d(st + 16384, &tm_x, kb * 64, tc * CT, b);
          tma2d(st + 8192, &tm_wu, ft * 64, kb * 64, b);
          mbar_expect(b + 64, HT1 * 128);
          tma2d(st + 16384 + G1_XB, &tm_x1, kb * 64, tc * CT + HT0, b + 64);
          st = st == sm + 2 * G1_STAGE ? sm : st + G1_STAGE;
        }
        if (mainc) {
          mbar_wait(bars + B_HST * 8);
          flag_wait(p.cnt + 64 + 32 * mt, NFT * ((mt * 128 + 127) / CT - (mt * 128) / CT + 1));
          fence_async_gmem();
          const uint4* src = p.h + mt * 128 * 8;
#pragma unroll 1
          for (int kb = 0; kb < NFT; kb++) {
            const uint32_t dst = sm + ((kb & 7) == 7 ? TAB : HRING + (kb & 7) * 16384), b = bars + (B_F2 + kb) * 8;
            if (kb >= 7) mbar_wait(bars + (kb == 7 ? B_CVD : B_D2 + kb - 7) * 8);
            mbar_expect(b, 16384);
            bulk_ld(dst, src, 16384, b);
            src += SEQ * 8;
          }
        }
      } else if (warp == 13) {
        if (mainc) {
#pragma unroll 1
          for (int i = 0; i < NFT; i++) {
            const int kb = i < 5 ? i + 1 : i == 5 ? 0 : i;
            const uint32_t b = bars + (B_F2 + kb) * 8;
            mbar_wait(bars + (i < 5 ? B_U : i == 5 ? B_D1 + 7 : i < 8 ? B_CVD : B_D2 + i - 7) * 8);
            mbar_expect(b, 8192);
            tma2d(sm + WRING + (kb & 7) * 8192, &tm_wd, dt * 64, kb * 64, b);
          }
        }
      } else if (warp == 14) {
        if (mainc) {
          if (lt2 < 17) p.cnt[32 + 32 * lt2] = 0;
          mbar_wait(bars + B_D1 * 8);
          l2_prefetch(p.wd + lt2 * 11008, 11008);
#pragma unroll
          for (int i = 0; i < 16; i++)
            asm volatile("cp.async.bulk.global.shared::cta.bulk_group [%0], [%1], 1024;" ::"l"(p.out + lt2 * 1024 + i * 64), "r"(sm + MEANS) : "memory");
          asm volatile("cp.async.bulk.commit_group;" ::: "memory");
          asm volatile("cp.async.bulk.wait_group 0;" ::: "memory");
          fence_async_gmem();
          mbar_wait(bars + B_LND * 8);
          flag_arrive(p.cnt);
        }
        flag_wait(p.cnt, NMAIN);
        fence_async_gmem();
        asm volatile("red.relaxed.gpu.global.add.u32 [%0], 1;" ::"l"(p.cnt + 32) : "memory");
        mbar_expect(bars + B_STAT * 8, 1408 + 512);
        bulk_ld(sm + MEANS, p.stat + tc * 352, 1408, bars + B_STAT * 8);
        bulk_ld(sm + R2S, p.stat + 12 * 176 + mt * 128, 512, bars + B_STAT * 8);
        if (mainc) {
          mbar_wait(bars + (B_D1 + 5) * 8);
          mbar_expect(bars + B_U * 8, 16384);
          bulk_ld(sm + UOFF + 1024, p.u + lt2 * UP * 8, 16384, bars + B_U * 8);
          mbar_wait(bars + B_CV1 * 8);
          mbar_expect(bars + B_X * 8, 16384);
          tma2d(sm + XT, &tm_x2, dt * 64, mt * 128, bars + B_X * 8);
          if (lt2 == 0) {
            flag_wait(p.cnt + 32, NCTA);
            p.cnt[0] = 0;
          }
        }
      } else {
        unsigned* hc = p.cnt + 64 + 32 * ((tc * CT) >> 7);
        const bool four = (min(tc * CT + CT - 1, SEQ - 1) >> 7) - ((tc * CT) >> 7) == 3;
        const uint4* hd = p.h + (ft * SEQ + tc * CT) * 8;
        const uint32_t last = (min(HT1, SEQ - tc * CT - HT0) - (NCH - 1) * HCH) * 128;
#pragma unroll
        for (int i = 0; i < 2 * NCH; i++) {
          const int wg = i / NCH, c = i % NCH, r0 = c * HCH;
          mbar_wait(bars + (B_STG + i) * 8);
          fence_async_smem();
          asm volatile("cp.async.bulk.global.shared::cta.bulk_group [%0], [%1], %2;"
                       ::"l"(hd + (wg * HT0 + r0) * 8), "r"(sm + 16384 + wg * G1_XB + r0 * 128), "r"(c < NCH - 1 ? HCH * 128 : wg ? last : (HT0 - r0) * 128) : "memory");
        }
        asm volatile("cp.async.bulk.commit_group;" ::: "memory");
        asm volatile("cp.async.bulk.wait_group 0;" ::: "memory");
        mbar_arrive(bars + B_HST * 8);
        fence_async_gmem();
        asm volatile("fence.release.gpu;" ::: "memory");
#pragma unroll
        for (int m = 0; m < 4; m++)
          if (m < 3 || four) asm volatile("red.relaxed.gpu.global.add.u32 [%0], 1;" ::"l"(hc + 32 * m) : "memory");
      }
    }
  } else if (warp >= 8) {
    asm volatile("setmaxnreg.dec.sync.aligned.u32 72;");
    const int w = warp & 3, tid = threadIdx.x & 127, g = lane >> 2, tq = lane & 3;
    sts32(sm + (w >> 1) * G1_STAGE + 16384 + (w & 1) * (G1_XB + 1024) + 167 * 128 + lane * 4, 0x3F803F80u);
    fence_async_smem();
    asm volatile("bar.arrive 6, 384;" ::: "memory");
    asm volatile("bar.arrive 7, 384;" ::: "memory");
    asm volatile("bar.sync 5, 256;" ::: "memory");
    if (mainc) {
      mbar_wait(bars + B_TD * 8);
      uint4 xv[8];
      const uint4* src = p.x + (lt2 * 16 + g * 2) * 64 + w * 16 + tq * 2;
#pragma unroll
      for (int i = 0; i < 8; i++)
        asm volatile("ld.global.nc.v4.u32 {%0,%1,%2,%3}, [%4];" : "=r"(xv[i].x), "=r"(xv[i].y), "=r"(xv[i].z), "=r"(xv[i].w) : "l"(src + (i >> 2) * 64 + ((i >> 1) & 1) * 8 + (i & 1)));
      const uint32_t* r = reinterpret_cast<const uint32_t*>(xv);
      float st[4];
#pragma unroll
      for (int h = 0; h < 2; h++) {
        float s0 = 0.f, s1 = 0.f, q0 = 0.f, q1 = 0.f;
#pragma unroll
        for (int i = 0; i < 16; i++) {
          const float a = blo(r[16 * h + i]), b = bhi(r[16 * h + i]);
          s0 += a; s1 += b; q0 = fmaf(a, a, q0); q1 = fmaf(b, b, q1);
        }
        st[2 * h] = s0 + s1; st[2 * h + 1] = q0 + q1;
      }
#pragma unroll
      for (int i = 0; i < 4; i++) { st[i] += __shfl_xor_sync(0xffffffffu, st[i], 1); st[i] += __shfl_xor_sync(0xffffffffu, st[i], 2); }
      if (tq == 0) sts128f(sm + LNP + w * 128 + g * 16, st[0], st[1], st[2], st[3]);
      bar_sync(3);
      lds128f(st, sm + LNP + g * 16);
#pragma unroll
      for (int i = 1; i < 4; i++) {
        float v[4];
        lds128f(v, sm + LNP + i * 128 + g * 16);
        st[0] += v[0]; st[1] += v[1]; st[2] += v[2]; st[3] += v[3];
      }
      uint32_t mb[2], ih[2], il[2];
      float r2[2];
#pragma unroll
      for (int h = 0; h < 2; h++) {
        const float mean = st[2 * h] * (1.f / DM);
        const float var = fmaxf(fmaf(-mean, mean, st[2 * h + 1] * (1.f / DM)), 0.f);
        float sd, inv;
        asm("sqrt.approx.ftz.f32 %0, %1;" : "=f"(sd) : "f"(rbf(rbf(var) + 1e-5f)));
        asm("rcp.approx.ftz.f32 %0, %1;" : "=f"(inv) : "f"(rbf(sd)));
        mb[h] = pack(mean, mean);
        ih[h] = pack(inv, inv);
        const float lo = inv - blo(ih[h]);
        il[h] = pack(lo, lo);
        r2[h] = inv * inv;
      }
      if (w == 0 && tq < 2) {
        const int t = lt2 * 16 + 2 * g + tq, c = t / CT, j0 = t - c * CT, j = j0 + (j0 >= HT0 ? 176 - HT0 : 0);
        p.stat[c * 352 + (j & ~14) + ((j & 6) << 1) + ((j & 8) >> 2)] = -blo(tq ? mb[1] : mb[0]);
        p.stat[12 * 176 + t] = tq ? r2[1] : r2[0];
      }
      uint32_t* dst = (uint32_t*)p.u + ((w * 32 + tq * 4) * UP + lt2) * 32;
      const uint32_t sw = ((lt2 & 7) << 2) ^ g;
#pragma unroll
      for (int j = 0; j < 16; j++) {
        const uint32_t a = norm2(r[j], mb[0], ih[0], il[0]), b = norm2(r[16 + j], mb[1], ih[1], il[1]);
        const int c = (j >> 3) * 16 + ((j >> 1) & 3);
        dst[c * UP * 32 + (((j & 1) * 16) ^ sw)] = __byte_perm(a, b, 0x5410);
        dst[c * UP * 32 + (((j & 1) * 16 + 8) ^ sw)] = __byte_perm(a, b, 0x7632);
      }
      const uint32_t k2048 = pack(__uint_as_float(lds32(sm + R2S + (tid & 3) * 8)) + __uint_as_float(lds32(sm + R2S + (tid & 3) * 8 + 4)), 0.f);
      asm volatile("" ::"r"(k2048) : "memory");
      warp_arrive(bars + B_LND * 8);
      mbar_wait(bars + B_KD * 8);
      {
        const uint32_t kc = sm + KC + (w >> 1) * 2, b = 16 * (w & 1) + g, h1 = tq < 2 ? 128 : 64;
        uint32_t ka0 = kc + (8 * b + 2 * tq) * 4, ka1 = kc + (tq < 2 ? 256 + 4 * b + 2 * tq : 256 + 64 * tq + 2 * b) * 4, ka2 = kc + (512 + 64 * (tq & 1) + b) * 4;
#pragma unroll 1
        for (int pr = 0; pr < 2; pr++) {
          uint32_t kv[6];
          lds128(kv, sm + KRAW + (pr * 128 + tid) * 16);
          asm volatile("ld.shared.v2.u32 {%0,%1}, [%2];" : "=r"(kv[4]), "=r"(kv[5]) : "r"(sm + KRAW + 4096 + (pr * 128 + tid) * 8) : "memory");
          sts16(ka0, kv[0]); sts16(ka0 + 4, kv[0] >> 16); sts16(ka0 + 256, kv[1]); sts16(ka0 + 260, kv[1] >> 16);
          sts16(ka1, kv[2]); sts16(ka1 + 4, kv[2] >> 16); sts16(ka1 + h1, kv[3]); sts16(ka1 + h1 + 4, kv[3] >> 16);
          if ((tq >> 1) == (w >> 1)) { sts16(ka2, kv[4]); sts16(ka2 + 128, kv[4] >> 16); sts16(ka2 + 32, kv[5]); sts16(ka2 + 160, kv[5] >> 16); }
          ka0 += 2816; ka1 += 2816; ka2 += 2816;
        }
        if (tid < 4) sts16(sm + KC + (tid >> 1) * 2816 + (tid & 1) * 2 + 640 * 4, k2048);
        bar_sync(3);
      }
      if (tid < 16) sts128(sm + TAB + (tid >> 3) * RND + ((tid >> 2) & 1) * PT + (tid & 3) * 16, 0, 0, 0, 0);
#pragma unroll 1
      for (int L0 = 4 * tid; L0 < 1040; L0 += 512) {
        uint32_t o[5];
#pragma unroll
        for (int j = 0; j < 5; j++) {
          const int l = L0 - 1 + j;
          const int rk = l < 128 ? max(l, 0) : (int)(pack((float)l, 0.f) - 0x4280u);
          o[j] = sm + KC + rk * 4;
        }
#pragma unroll
        for (int pr = 0; pr < 2; pr++) {
          uint32_t k[5];
#pragma unroll
          for (int j = 0; j < 5; j++) {
            k[j] = lds32(o[j] + pr * 2816);
            if ((uint32_t)(L0 - 1 + j) > 1028u) k[j] = 0;
          }
          const uint32_t a = sm + TAB + (1 - pr) * RND + (16 + L0 + (L0 >> 7) * 24) * 4;
#pragma unroll
          for (int c = 0; c < 2; c++) {
            const uint32_t sel = c ? 0x7632 : 0x5410;
            const uint32_t q0 = __byte_perm(k[1], k[0], sel), q1 = __byte_perm(k[2], k[1], sel), q2 = __byte_perm(k[3], k[2], sel), q3 = __byte_perm(k[4], k[3], sel);
            sts128(a + c * PT, q0, q1, q2, q3);
            if (lane >= 28) sts128(a + c * PT + 96, q0, q1, q2, q3);
          }
        }
      }
#pragma unroll 1
      for (int pr = 0; pr < 2; pr++) {
        uint32_t k[8];
        const int x = tid & 63;
#pragma unroll
        for (int j = 0; j < 8; j++) {
          k[j] = lds32(sm + KC + pr * 2816 + (514 - (tid >> 6) + 2 * (x - j)) * 4);
          if (x < j) k[j] = 0;
        }
        const uint32_t a = sm + TAB + (1 - pr) * RND + PSZ + tid * 16;
        sts128(a, __byte_perm(k[0], k[1], 0x5410), __byte_perm(k[2], k[3], 0x5410), __byte_perm(k[4], k[5], 0x5410), __byte_perm(k[6], k[7], 0x5410));
        sts128(a + PT, __byte_perm(k[0], k[1], 0x7632), __byte_perm(k[2], k[3], 0x7632), __byte_perm(k[4], k[5], 0x7632), __byte_perm(k[6], k[7], 0x7632));
      }
      mbar_wait(bars + (B_D1 + 5) * 8);
      if (tid < 64) sts128(sm + UOFF + tid * 16, 0, 0, 0, 0);
      fence_async_smem();
      bar_sync(3);
      mbar_wait(bars + B_U * 8);
    }
    mbar_wait(bars + B_STAT * 8);
    warp_arrive(bars + B_P * 8);
    if (mainc) {
      mbar_wait(bars + (B_STG + NCH - 1) * 8);
      float c[48];
      c[0] = 0.f;
#pragma unroll
      for (int q = 0; q < 7; q++) {
        const int row = 6 + 2 * lane + ((q + 1) >> 1);
        uint32_t v[4];
        lds128(v, sm + UOFF + row * 128 + (((2 * w + ((q + 1) & 1)) ^ (row & 7)) << 4));
#pragma unroll
        for (int e = 0; e < 8; e++) {
          const int i = 8 * q + e - 4;
          if (i >= 0 && i < 47) c[i + 1] = c[i] + ((e & 1) ? bhi(v[e >> 1]) : blo(v[e >> 1]));
        }
      }
      const uint32_t wa = sm + TAB + (1 - (w >> 1)) * RND + WOFF + (w & 1) * 4096 + (lane >> 4) * 2048 + (lane & 15) * 16;
#pragma unroll
      for (int q = 0; q < 8; q++)
        sts128((wa ^ ((q & 1) * 64)) + q * 256, pack(c[q + 9] - c[q], c[q + 25] - c[q + 16]), pack(c[q + 17] - c[q + 8], c[q + 33] - c[q + 24]),
               pack(c[q + 16] - c[q + 9], c[q + 32] - c[q + 25]), pack(c[q + 24] - c[q + 17], c[q + 40] - c[q + 33]));
      warp_arrive(bars + B_W * 8);
    }
    if (mainc) {
      asm volatile("setmaxnreg.inc.sync.aligned.u32 120;");
      float acc[64];
      const uint64_t db0 = p.d128 + (sm + HRING) / 16, da0 = p.dq[0] + (sm + WRING) / 16;
      uint32_t ga = sm + GT + ((lane & 7) + (lane >> 4) * 8) * 128 + (((2 * w + ((lane >> 3) & 1)) ^ (lane & 7)) << 4);
      asm volatile("" : "+r"(ga));
      mbar_wait(bars + B_F2 * 8);
      asm volatile("bar.sync 11, 384;" ::: "memory");
      asm volatile(".reg .pred g2_next;");
#pragma unroll 1
      for (int kb = 0; kb < NFT - 1; kb++) {
        const uint64_t da = da0 + (kb & 7) * 512, db = db0 + ((kb & 7) == 7 ? (TAB - HRING) / 16 : (kb & 7) * 1024);
        const uint32_t nb = bars + (B_F2 + kb + 1) * 8;
        asm volatile("mbarrier.test_wait.parity.shared::cta.b64 g2_next, [%0], 0;" ::"r"(nb) : "memory");
        WG_FENCE();
#pragma unroll
        for (int ks = 0; ks < 4; ks++) wgmma_ss_n128<1, 0>(acc, da + 128 * ks, db + 2 * ks, ks ? 1 : kb);
        WG_COMMIT();
        wg_wait<1>();
        if (elect()) mbar_arrive(bars + (B_D2 + kb) * 8);
        asm volatile(
            "{\n.reg .pred p;\n.reg .u32 c;\n@g2_next bra D_%=;\nmov.u32 c, 0;\n"
            "W_%=:\nmbarrier.try_wait.parity.shared::cta.b64 p, [%0], 0;\n@p bra D_%=;\n"
            "add.u32 c, c, 1;\nsetp.lt.u32 p, c, 0x40000;\n@p bra W_%=;\ntrap;\nD_%=:\n}\n" ::"r"(nb) : "memory");
      }
      WG_FENCE();
      wgmma_ss_n128<1, 0>(acc, da0 + 5 * 512, db0 + 5 * 1024, 1);
      wgmma_ss_n128<1, 0>(acc, da0 + (5 * 512 + 128), db0 + (5 * 1024 + 2), 1);
      WG_COMMIT();
      wg_wait<0>();
      pin<64>(acc);
#pragma unroll
      for (int i = 0; i < 8; i++) {
        const int jp = (i & 3) * 2 + (i >> 2);
        asm volatile("stmatrix.sync.aligned.m8n8.x4.trans.shared.b16 [%0], {%1,%2,%3,%4};" ::"r"(ga + jp * 2048), "r"(pack(acc[8 * jp], acc[8 * jp + 1])),
                     "r"(pack(acc[8 * jp + 2], acc[8 * jp + 3])), "r"(pack(acc[8 * jp + 4], acc[8 * jp + 5])), "r"(pack(acc[8 * jp + 6], acc[8 * jp + 7])) : "memory");
        if ((i & 3) == 3) asm volatile("bar.arrive %0, 384;" ::"r"(12 + i / 4) : "memory");
      }
    }
  } else {
    const int wg = warp >> 2, w = warp & 3, tq = lane & 3;
    uint32_t kv[6];
    const uint32_t ta = sm + KTAB + (warp / 4 * 4 + (warp & 1) * 2) * KSL + (warp & 2) * 2048 + lane * 4;
    const uint32_t ob = 8192 - (warp & 2) * 1024, oc = 12288 - (warp & 2) * 2048;
    uint32_t tx[8], ty[4];
#pragma unroll
    for (int i = 0; i < 8; i++) { tx[i] = (ta ^ (i << 4)) + i * 128; asm volatile("" : "+r"(tx[i])); }
#pragma unroll
    for (int i = 0; i < 4; i++) { ty[i] = ((warp & 2) ? tx[4 + i] : tx[i]) + oc; asm volatile("" : "+r"(ty[i])); }
    asm volatile("setmaxnreg.inc.sync.aligned.u32 208;");
    if (!mainc) {
      asm volatile("bar.sync %0, 384;" ::"r"(6 + wg) : "memory");
    } else {
#pragma unroll
      for (int i = 0; i < 10; i++) asm volatile("" : "+r"(prm[i]));
      asm volatile("" : "+r"(ldt));
      const float dtv = rbf(expf(blo(ldt)));
      const uint32_t eb = max_exp(prm[2], prm[3], prm[6], prm[7]), ec = max_exp(prm[4], prm[5], prm[8], prm[9]);
      const float sb = __uint_as_float((260 - eb) << 23), sc = __uint_as_float((259 - ec) << 23);
      const float kscale = dtv * __uint_as_float((eb - 6) << 23), kscale2 = __uint_as_float((ec - 5) << 23);
#define STA(row, v) stc(tx[row] + oa, v)
#define STB(row, v) stc(tx[(row) & 7] + ob + ((row) >> 3) * 1024, v)
      float al[2], th[2];
      cplx z1[2], z2[2], z4[2], z8[2], z16[2], z32[2], z64[2], w1[2], w2[2], w4[2], w8[2], a[2];
#pragma unroll
      for (int e = 0; e < 2; e++) {
        al[e] = (dtv * 1.4426950408889634f) * (e ? bhi(prm[0]) : blo(prm[0]));
        th[e] = (dtv * 0.15915494309189535f) * (e ? bhi(prm[1]) : blo(prm[1]));
        z1[e] = cexp2(al[e], th[e]); z2[e] = csq(z1[e]); z4[e] = csq(z2[e]);
      }
      const cplxh x1 = toh(z1[0], z1[1]), x2 = toh(z2[0], z2[1]), x4 = toh(z4[0], z4[1]), x6 = hmul(x4, x2);
      STB(0, CH_ONE); STB(1, x1); STB(2, x2); STB(3, hmul(x2, x1)); STB(4, x4); STB(5, hmul(x4, x1)); STB(6, x6); STB(7, hmul(x6, x1));
#pragma unroll
      for (int e = 0; e < 2; e++) {
        z32[e] = cexp2(al[e] * 32.f, th[e] * 32.f); z64[e] = csq(z32[e]);
        w1[e] = csq(csq(z64[e])); w2[e] = csq(w1[e]); w4[e] = csq(w2[e]); w8[e] = csq(w4[e]);
      }
      {
        const cplxh u1 = toh(w1[0], w1[1]), u2 = toh(w2[0], w2[1]), u4 = toh(w4[0], w4[1]), u3 = hmul(u2, u1);
        STB(8, u1); STB(9, hmul(u1, x2)); STB(10, hmul(u1, x4)); STB(11, hmul(u1, x6));
        STB(12, u2); STB(13, hmul(u2, x4)); STB(14, u3); STB(15, hmul(u3, x4));
        stc(ty[0], u4); stc(ty[1], hmul(u4, u1)); stc(ty[2], hmul(u4, u2)); stc(ty[3], hmul(u4, u3));
      }
#pragma unroll
      for (int e = 0; e < 2; e++) {
        float v[4];
#pragma unroll
        for (int i = 0; i < 4; i++) v[i] = e ? bhi(prm[2 + i]) : blo(prm[2 + i]);
        z8[e] = csq(z4[e]); z16[e] = csq(z8[e]);
        a[e] = cmul({v[2] * sc, -v[3] * sc}, {v[0] * sb, -v[1] * sb});
      }
      {
        float k = fmaf(a[0].x, w8[0].x, a[0].y * w8[0].y) + fmaf(a[1].x, w8[1].x, a[1].y * w8[1].y);
#pragma unroll
        for (int o = 16; o; o >>= 1) k += __shfl_xor_sync(0xffffffffu, k, o);
        if (lane == 0) sts32(sm + R2S + warp * 4, __float_as_uint(k * kscale * kscale2));
      }
      const cplxh y1 = toh(z8[0], z8[1]), y2 = toh(z16[0], z16[1]), y4 = toh(z32[0], z32[1]);
#pragma unroll 1
      for (uint32_t oa = 0; oa < 4096; oa += 1024) {
        const cplxh r0 = toh(a[0], a[1]), r4 = hmulc(r0, y4), r2 = hmulc(r0, y2), r6 = hmulc(r4, y2);
        STA(0, r0); STA(4, r4); STA(2, r2); STA(1, hmulc(r0, y1)); STA(6, r6); STA(3, hmulc(r2, y1)); STA(5, hmulc(r4, y1)); STA(7, hmulc(r6, y1));
        a[0] = cmulc(a[0], z64[0]); a[1] = cmulc(a[1], z64[1]);
      }
#undef STA
#undef STB
      fence_async_smem();
      asm volatile("bar.sync %0, 384;" ::"r"(6 + wg) : "memory");
      float acc[20];
      const uint64_t da = p.d128 + ((sm + KTAB) / 16 + wg * (4 * KSL / 16));
      if (wg) asm volatile("bar.sync 4, 256;" ::: "memory");
      WG_FENCE();
#pragma unroll
      for (int ks = 0; ks < 16; ks++) wgmma_ss_n40_f16<0, 0>(acc, da + ((ks >> 2) * (KSL / 16) + (ks & 3) * 2), da + (512 + (ks >> 2) * (KSL / 16) + (ks & 3) * 2), ks);
      WG_COMMIT();
      if (!wg) asm volatile("bar.arrive 4, 256;" ::: "memory");
      asm volatile("" : "+r"(dsk));
      const float d0 = (threadIdx.x & 63) == 0 ? blo(dsk) : 0.f;
      wg_wait<0>();
      pin<20>(acc);
      if (elect()) mbar_arrive(bars + B_TD * 8);
      if (w >> 1) {
#pragma unroll
        for (int i = 0; i < 8; i++) acc[i] = acc[8 + i];
      }
#pragma unroll
      for (int i = 0; i < 6; i++) {
        const int j = i < 4 ? 2 * i : 2 * i + 8;
        kv[i] = pack(fmaf(acc[j] * kscale, kscale2, i ? 0.f : d0), acc[j + 1] * kscale * kscale2);
      }
    }
    {
      float ag[88], au[88];
      uint32_t st = 0;
#pragma unroll 1
      for (int kb = 0; kb < 6; kb++) {
        const uint64_t da = p.d128 + (sm / 16 + st), db = da + (1024 + wg * (G1_XB / 16));
        mbar_wait(bars + (B_FA + kb) * 8);
        if (wg) mbar_wait(bars + (B_FB + kb) * 8);
        if (!wg) { WG_FENCE(); g1_steps<true>(ag, au, da, db, kb); WG_COMMIT(); }
        else { WG_FENCE(); g1_steps<false>(ag, au, da, db, kb); WG_COMMIT(); }
        st = st == 2 * G1_STAGE / 16 ? 0 : st + G1_STAGE / 16;
        if (kb == 0 && mainc) {
          mbar_wait(bars + B_TD * 8);
          sts128(sm + KRAW + threadIdx.x * 16, kv[0], kv[1], kv[2], kv[3]);
          asm volatile("st.shared.v2.u32 [%0], {%1,%2};" ::"r"(sm + KRAW + 4096 + threadIdx.x * 8), "r"(kv[4]), "r"(kv[5]) : "memory");
          warp_arrive(bars + B_KD * 8);
        }
        wg_wait<0>();
        if (elect()) mbar_arrive(bars + (B_D1 + kb) * 8);
      }
      {
        if (wg) { mbar_wait(bars + (B_FB + 6) * 8); mbar_wait(bars + (B_FB + 7) * 8); asm volatile("bar.sync 4, 256;" ::: "memory"); }
#pragma unroll
        for (int kb = 6; kb < 8; kb++) {
          const uint64_t da = p.dq[0] + (sm + (kb - 6) * G1_STAGE) / 16, db = da + (1024 + wg * (G1_XB / 16));
          if (!wg) mbar_wait(bars + (B_FA + kb) * 8);
          if (!wg) { WG_FENCE(); g1_steps<true>(ag, au, da, db, 1); WG_COMMIT(); }
          else { WG_FENCE(); g1_steps<false>(ag, au, da, db, 1); WG_COMMIT(); }
        }
        if (!wg) asm volatile("bar.arrive 4, 256;" ::: "memory");
        mbar_wait(bars + (wg ? B_P : B_STAT) * 8);
        wg_wait<0>();
        if (elect()) mbar_arrive(bars + (B_D1 + 7) * 8);
      }
      bar_sync(1 + wg);
      pin<88>(ag);
      pin<88>(au);
      const float cg0 = __shfl_sync(0xffffffffu, wg ? ag[85] : ag[81], lane | 3), cg1 = __shfl_sync(0xffffffffu, wg ? ag[87] : ag[83], lane | 3);
      const float cu0 = __shfl_sync(0xffffffffu, wg ? au[85] : au[81], lane | 3), cu1 = __shfl_sync(0xffffffffu, wg ? au[87] : au[83], lane | 3);
      const int tok0 = tc * CT + wg * HT0;
      const uint32_t sa = sm + 16384 + wg * G1_XB + ((lane & 7) + (lane >> 4) * 8) * 128 + (((2 * w + ((lane >> 3) & 1)) ^ ((tok0 + lane) & 7)) << 4);
      const uint32_t ma = sm + MEANS + wg * 704 + tq * 16;
      float mn[2][4];
      lds128f(mn[0], ma);
#pragma unroll
      for (int jp = 0; jp < 11; jp++) {
        uint32_t r[4];
        const float* m = mn[jp & 1];
        if (jp < 10) lds128f(mn[(jp & 1) ^ 1], ma + (jp + 1) * 64);
#pragma unroll
        for (int e = 0; e < 2; e++) {
          const int j = 2 * jp + e;
          const float m0 = m[2 * e], m1 = m[2 * e + 1];
          r[2 * e] = pack(fmaf(m0, cg0, ag[4 * j]) * fmaf(m0, cu0, au[4 * j]), fmaf(m1, cg0, ag[4 * j + 1]) * fmaf(m1, cu0, au[4 * j + 1]));
          r[2 * e + 1] = pack(fmaf(m0, cg1, ag[4 * j + 2]) * fmaf(m0, cu1, au[4 * j + 2]), fmaf(m1, cg1, ag[4 * j + 3]) * fmaf(m1, cu1, au[4 * j + 3]));
        }
        asm volatile("stmatrix.sync.aligned.m8n8.x4.trans.shared.b16 [%0], {%1,%2,%3,%4};" ::"r"(sa + jp * 2048), "r"(r[0]), "r"(r[1]), "r"(r[2]), "r"(r[3]) : "memory");
        if (jp == 8 && !wg) mbar_wait(bars + B_P * 8);
        if (jp == 10 || (jp + 1) * 16 % HCH == 0) {
          warp_arrive(bars + (B_STG + wg * NCH + jp * 16 / HCH) * 8);
        }
      }
    }
    if (mainc) {
      asm volatile("setmaxnreg.dec.sync.aligned.u32 184;");
      int lane;
      asm volatile("mov.u32 %0, %%laneid;" : "=r"(lane));
      const int g = lane >> 2, tq = lane & 3;
      {
        const uint32_t zero = lds32(sm + UOFF);
        uint32_t pa = sm + TAB + RND + wg * PT + (8 + 152 * (lane >> 3) + 2 * w + (g & 1) - 2 * tq) * 4;
        uint32_t wa = sm + TAB + RND + WOFF + wg * 4096 + (2 * w + (g & 1)) * 256 + ((((lane >> 3) * 4 + tq) ^ ((g & 1) * 4)) << 4);
#pragma unroll 1
        for (int cc = 0; cc < 2; cc++) {
          uint2* yo = (uint2*)p.out + ((lane >> 3) * 128 + (2 * w + (g & 1)) * 16 + ((lt2 & 1) * 4 + cc * 2 + wg) * 2 + ((lt2 & 15) >> 3)) * 128 + (lt2 >> 4) * 16 + (lt2 & 6) * 2 + tq;
          const uint32_t uo = (sm + UOFF) / 16 + (cc * 2 + wg) * 2;
          const uint64_t db = p.d128 + uo, db1 = p.dq[0] + uo, db2 = p.dq[1] + uo;
          const uint64_t dtt = p.dq[2] + ((sm + TAB + RND + PSZ) / 16 + wg * (PT / 16) - cc * (RND / 16));
          float acc[4][16];
          uint32_t R0[32], R1[32], RF[16], prev[6];
          conv_loadA<0>(R0, pa, zero);
          WG_FENCE(); conv_mma<0, 0, 2>(acc, R0, db);
          conv_loadA<1>(R1, pa, zero);
          conv_mma<0, 2, 5>(acc, R0, db);
          if (!cc) mbar_wait(bars + B_W * 8);
          {
            asm volatile("{\n.reg .pred q;\nsetp.lt.u32 q, %4, 8;\nmov.u32 %0, 0;\nmov.u32 %1, 0;\nmov.u32 %2, 0;\n"
                         "@q ld.shared.u32 %0, [%3+4896];\n@q ld.shared.u32 %1, [%3+4928];\n@q ld.shared.u32 %2, [%3+4864];\n}\n"
                         : "=&r"(RF[0]), "=&r"(RF[1]), "=&r"(RF[2]) : "r"(pa), "r"(lane));
            lds128(RF + 8, wa);
            lds128(RF + 12, wa + 2048);
            asm volatile("or.b32 %0, %1, %2;" : "=r"(RF[3]) : "r"(RF[0]), "r"(zero));
            asm volatile("or.b32 %0, %1, %2;" : "=r"(RF[6]) : "r"(RF[1]), "r"(zero));
            asm volatile("add.u32 %0, %1, %1;" : "=r"(RF[4]) : "r"(zero));
            asm volatile("shl.b32 %0, %1, 2;" : "=r"(RF[5]) : "r"(zero));
            asm volatile("shl.b32 %0, %1, 3;" : "=r"(RF[7]) : "r"(zero));
          }
          conv_mma<0, 5, 8>(acc, R0, db); WG_COMMIT();
          WG_FENCE();
          conv_mma<2, 0, 2>(acc, RF, db2);
          wgmma_rs_n32<0>(acc[2], RF[8], RF[9], RF[10], RF[11], dtt, 1);
          wgmma_rs_n32<0>(acc[3], RF[8], RF[9], RF[10], RF[11], dtt + 32, 1);
          wgmma_rs_n32<0>(acc[3], RF[12], RF[13], RF[14], RF[15], dtt, 1);
          if (cc && wg) {
            WG_COMMIT();
            WG_FENCE();
            conv_mma<1, 0, 8>(acc, R1, db1); WG_COMMIT();
            asm volatile("bar.arrive 11, 384;" ::: "memory");
            wg_wait<0>();
            if (elect()) mbar_arrive(bars + B_CVD * 8);
            conv_red<0>(acc, prev, lane, yo);
            conv_red<1>(acc, prev, lane, yo);
            conv_red<2>(acc, prev, lane, yo);
            conv_red<3>(acc, prev, lane, yo);
          } else {
            WG_COMMIT();
            WG_FENCE();
            conv_mma_blk<1, 1>(acc, R1, db1); WG_COMMIT();
            wg_wait<1>();
            conv_red<0>(acc, prev, lane, yo);
            conv_mma_blk<1, 2>(acc, R1, db1); WG_COMMIT();
            wg_wait<1>();
            conv_red<1>(acc, prev, lane, yo);
            conv_mma_blk<1, 3>(acc, R1, db1); WG_COMMIT();
            if (cc) asm volatile("bar.arrive 11, 384;" ::: "memory");
            wg_wait<1>();
            conv_red<2>(acc, prev, lane, yo);
            wg_wait<0>();
            if (elect()) mbar_arrive(bars + (B_CV1 + cc) * 8);
            conv_red<3>(acc, prev, lane, yo);
          }
          pa -= RND;
          wa -= RND;
        }
      }
      {
        mbar_wait(bars + (B_D2 + 1) * 8);
        const uint2* ys = (const uint2*)p.out + (mt * 128 + warp * 16 + ((lane & 7) >> 2)) * 128 + dt * 16 + (lane & 3) * 4 + (lane >> 3);
        const int row = (lane >> 3) * 32 + warp;
        uint32_t oa = sm + row * 128 + (((lane & 7) ^ warp) << 4);
        uint4* dst = p.out + (mt * 128 + row) * 64 + dt * 8 + (lane & 7);
        uint32_t y[16], x[16], rh[4], rl[4];
        mbar_wait(bars + B_X * 8);
#pragma unroll
        for (int i = 0; i < 4; i++) {
          lds128(x + 4 * i, oa + XT + i * 1024);
          const float r = __uint_as_float(lds32(sm + R2S + (row + 8 * i) * 4));
          rh[i] = pack(r, r);
          rl[i] = pack(r - blo(rh[i]), r - blo(rh[i]));
          asm volatile("" : "+r"(rh[i]), "+r"(rl[i]));
        }
        asm volatile("" : "+r"(oa), "+l"(dst));
        mbar_wait(bars + (B_D2 + 15) * 8);
        y_poll(y, ys);
#pragma unroll
        for (int i = 0; i < 16; i++) {
          x[i] = badd2(x[i], __byte_perm(y[(i >> 3) * 8 + (i & 3) * 2], y[(i >> 3) * 8 + (i & 3) * 2 + 1], (i & 4) ? 0x7632 : 0x5410));
          asm volatile("" : "+r"(x[i]));
        }
#pragma unroll
        for (int hf = 0; hf < 2; hf++) {
          asm volatile("bar.sync %0, 384;" ::"r"(12 + hf) : "memory");
#pragma unroll
          for (int i = 2 * hf; i < 2 * hf + 2; i++) lds128(y + 4 * i, oa + GT + i * 1024);
#pragma unroll
          for (int i = 2 * hf; i < 2 * hf + 2; i++) {
            uint32_t v[4];
#pragma unroll
            for (int e = 0; e < 4; e++) v[e] = bfma2(y[4 * i + e], rh[i], bfma2(y[4 * i + e], rl[i], x[4 * i + e]));
            asm volatile("st.global.v4.u32 [%0], {%1,%2,%3,%4};" ::"l"(dst + i * 8 * 64), "r"(v[0]), "r"(v[1]), "r"(v[2]), "r"(v[3]) : "memory");
          }
        }
      }
    }
  }
}

typedef CUresult (*EncodeFn)(CUtensorMap*, CUtensorMapDataType, cuuint32_t, void*, const cuuint64_t*, const cuuint64_t*, const cuuint32_t*,
                             const cuuint32_t*, CUtensorMapInterleave, CUtensorMapSwizzle, CUtensorMapL2promotion, CUtensorMapFloatOOBfill);

void make_map(EncodeFn enc, CUtensorMap* m, const void* base, uint64_t cols, uint64_t rows, uint32_t box_rows) {
  cuuint64_t dims[2] = {cols, rows}, strides[1] = {cols * 2};
  cuuint32_t box[2] = {64, box_rows}, es[2] = {1, 1};
  enc(m, CU_TENSOR_MAP_DATA_TYPE_BFLOAT16, 2, const_cast<void*>(base), dims, strides, box, es, CU_TENSOR_MAP_INTERLEAVE_NONE,
      CU_TENSOR_MAP_SWIZZLE_128B, CU_TENSOR_MAP_L2_PROMOTION_L2_128B, CU_TENSOR_MAP_FLOAT_OOB_FILL_NONE);
}

}

extern "C" void kernel_launch(void* const* d_in, const int* in_sizes, int n_in, void* d_out, int out_size) {
  static EncodeFn enc = nullptr;
  static int sms = 0;
  if (!enc) {
    void* fn = nullptr;
    cudaDriverEntryPointQueryResult q;
    cudaGetDriverEntryPoint("cuTensorMapEncodeTiled", &fn, cudaEnableDefault, &q);
    enc = (EncodeFn)fn;
    cudaFuncSetAttribute(fused_kernel<true>, cudaFuncAttributeMaxDynamicSharedMemorySize, SMEM_BYTES);
    cudaFuncSetAttribute(fused_kernel<false>, cudaFuncAttributeMaxDynamicSharedMemorySize, SMEM_BYTES);
    int dev = 0;
    cudaGetDevice(&dev);
    cudaDeviceGetAttribute(&sms, cudaDevAttrMultiProcessorCount, dev);
  }
  CUtensorMap tx, tx1, twg, twu, twd, tx2;
  make_map(enc, &tx, d_in[0], DM, SEQ, HT0);
  make_map(enc, &tx1, d_in[0], DM, SEQ, HT1);
  make_map(enc, &twg, d_in[10], FF, DM, 64);
  make_map(enc, &twu, d_in[11], FF, DM, 64);
  make_map(enc, &twd, d_in[12], DM, FF, 64);
  make_map(enc, &tx2, d_in[0], DM, SEQ, 128);
  Params p;
  p.x = (const uint4*)d_in[0];
  p.d128 = p.dq[0] = p.dq[1] = D128;
  p.dq[2] = (8ull << 32) | (64ull << 16);
  p.out = (uint4*)d_out;
  cudaGetSymbolAddress((void**)&p.h, g_h); cudaGetSymbolAddress((void**)&p.u, g_u);
  cudaGetSymbolAddress((void**)&p.stat, g_stat); cudaGetSymbolAddress((void**)&p.cnt, g_cnt);
  for (int i = 0; i < 6; i++) p.ssm[i] = (const uint32_t*)d_in[1 + i];
  p.logdt = (const uint16_t*)d_in[7]; p.dskip = (const uint16_t*)d_in[8];
  p.wg = (const uint8_t*)d_in[10]; p.wu = (const uint8_t*)d_in[11]; p.wd = (const uint8_t*)d_in[12];
  for (int id = 0; id < NCTA; id++) {
    const int tpc = id >> 1;
    int lt;
    if (tpc < 32) lt = (tpc & 7) ? ((tpc & 7) - 1) * 8 + (tpc >> 3) : 56 + (tpc >> 3);
    else if (tpc < 60) lt = ((tpc - 32) % 7) * 8 + 4 + (tpc - 32) / 7;
    else lt = tpc < 62 ? tpc + 4 : tpc - 2;
    p.role[id] = (lt % NFT) | ((lt / NFT) * 2 + (id & 1)) << 8 | ((((lt >> 3) & 7) * 2 + (id & 1)) << 16) | (lt & 7) << 24;
  }
  cudaLaunchConfig_t cfg = {};
  cudaLaunchAttribute at;
  at.id = cudaLaunchAttributeCooperative;
  at.val.cooperative = 1;
  cfg.gridDim = NCTA; cfg.blockDim = 512; cfg.dynamicSmemBytes = SMEM_BYTES; cfg.stream = cudaStreamPerThread;
  cfg.attrs = &at; cfg.numAttrs = 1;
  cudaLaunchKernelEx(&cfg, sms == NCTA ? fused_kernel<true> : fused_kernel<false>, p, tx, tx1, twg, twu, twd, tx2);
}
```
